```python
import torch

def _softmax(x, axis=-1):
    return torch.softmax(x, dim=axis)
def _gelu(x):
    return torch.nn.functional.gelu(x, approximate="tanh")
def _silu(x):
    return torch.nn.functional.silu(x)
def _sigmoid(x):
    return torch.sigmoid(x)
def _layernorm(x, axis=-1, eps=1e-5):
    m = x.mean(dim=axis, keepdim=True)
    v = x.var(dim=axis, keepdim=True, unbiased=False)
    return (x - m) / torch.sqrt(v + eps)
def _scatter_add(tgt, idx, src, axis=0):
    return tgt.clone().index_add_(axis, idx, src)
def _segment_sum(src, seg, n):
    out = torch.zeros((n,) + src.shape[1:], dtype=src.dtype)
    return out.index_add_(0, seg, src)
def _pad(x, pw):
    flat = tuple(v for pair in reversed(pw) for v in pair)
    return torch.nn.functional.pad(x, flat)

kernel_name = 'standalone__edge_featured_mpnn_egc__graph'

def setup_inputs():

    _w = (lambda a: (lambda t: t.to(torch.bfloat16) if t.is_floating_point() else t)(torch.as_tensor(a)))
    N, deg, D, De = 10000, 16, 256, max(16, 1)
    E = N * deg
    return {
        "x": _w((lambda *s: torch.randn(*s, dtype=torch.bfloat16) * 0.1)(N, D)),
        "e_attr": _w((lambda *s: torch.randn(*s, dtype=torch.bfloat16) * 0.1)(E, De)),
        "src": _w((lambda lo, hi, *s: torch.randint(lo, hi, s))(0, N, E).to(torch.int64)),
        "dst": _w((lambda lo, hi, *s: torch.randint(lo, hi, s))(0, N, E).to(torch.int64)),
        "u_w": _w((lambda *s: torch.randn(*s, dtype=torch.bfloat16) * 0.05)(D, D)),
        "v_w": _w((lambda *s: torch.randn(*s, dtype=torch.bfloat16) * 0.05)(D, D)),
        "g_w": _w((lambda *s: torch.randn(*s, dtype=torch.bfloat16) * 0.1)(2 * D + De, D)),
    }

def reference(x, e_attr, src, dst, u_w, v_w, g_w):
    N, D = x.shape
    g_in = torch.concatenate([x[dst], x[src], e_attr], axis=-1)
    eta = _sigmoid(g_in @ g_w)
    hv = x @ v_w
    msg = eta * hv[src]
    agg = _segment_sum(msg, dst, N)
    return _silu(x @ u_w + agg)
```

```cpp
#include <cuda_runtime.h>
#include <cuda_bf16.h>
#include <cuda.h>
#include <stdint.h>

namespace egc {

constexpr int NN = 10000;
constexpr int DD = 256;
constexpr int TILE = 80;
constexpr int NT = 125;
constexpr int EPC = 1280;
constexpr int NST = 3;
constexpr int NIT = 16;
#define EGC_HINT 20000
#define EGC_X_EARLY 2
constexpr int X_EARLY = EGC_X_EARLY;
constexpr int CAP_STEPS = 98;

constexpr int N_MAIN = 512, N_AUX = 128;
constexpr int NTHREADS = N_MAIN + N_AUX + 128;

constexpr int X_OFF = 0;
constexpr int RING_OFF = 40960;
constexpr int PARK_ACC = 0;
constexpr int PARK_XA = 81920;
constexpr int EATTR_OFF = RING_OFF + NST * 32768;
constexpr int CAND_OFF = EATTR_OFF + CAP_STEPS * 512;
constexpr int MR_OFF = CAND_OFF + 16384;
constexpr int MQ_OFF = MR_OFF + (CAP_STEPS + 2) * 128;
constexpr int CAPG = 192;
constexpr int EL_OFF = MQ_OFF + CAP_STEPS * 32;
constexpr int ER_OFF = EL_OFF + 10 * CAPG * 4;
constexpr int CNT_OFF = ER_OFF + 10 * CAPG;
constexpr int MISC_OFF = CNT_OFF + 512;
constexpr int BAR_OFF = MISC_OFF + 128;
constexpr int SMEM_BYTES = BAR_OFF + 128;
static_assert(PARK_XA + 40960 <= EATTR_OFF, "parking area must fit in x + ring");
static_assert(SMEM_BYTES <= 232448, "too much shared memory");

constexpr uint32_t REC_INV = 0x7FFFFFFFu, REC_OVF = 0x7E000000u;
__device__ __forceinline__ uint32_t rec_dl(uint32_t w) { return (w >> 24) & 127; }
constexpr uint32_t DBF_INV = 0x4380u;

constexpr int BAR_AUX = 1, BAR_MAIN = 2, BAR_READY = 3, BAR_CONSUMED = 4, BAR_TABLE = 5, BAR_GO = 6, BAR_S1 = 7, BAR_STG = 8, BAR_XFREE = 9;

__device__ uint4 g_tab[(size_t)NN * 64];
__device__ uint4 g_slots[(size_t)NT * NT * 8];
__device__ unsigned int g_bar[64];
#define PROF(i) do { } while (0)
#define PROF2(i) do { } while (0)

__device__ __forceinline__ void bar_sync(int id, int n) { asm volatile("bar.sync %0, %1;" ::"r"(id), "r"(n) : "memory"); }
__device__ __forceinline__ void bar_arrive(int id, int n) { asm volatile("bar.arrive %0, %1;" ::"r"(id), "r"(n) : "memory"); }

__device__ __forceinline__ void mbar_init(uint32_t bar, uint32_t cnt) {
    asm volatile("mbarrier.init.shared::cta.b64 [%0], %1;" ::"r"(bar), "r"(cnt) : "memory");
}
__device__ __forceinline__ void mbar_expect_tx(uint32_t bar, uint32_t bytes) {
    asm volatile("mbarrier.arrive.expect_tx.shared::cta.b64 _, [%0], %1;" ::"r"(bar), "r"(bytes) : "memory");
}
__device__ __forceinline__ void mbar_arrive(uint32_t bar) {
    asm volatile("mbarrier.arrive.shared::cta.b64 _, [%0];" ::"r"(bar) : "memory");
}
__device__ __forceinline__ void mbar_wait(uint32_t bar, uint32_t parity) {
    uint32_t ok;
    int spins = 0;
    do {
        asm volatile("{\n.reg .pred p;\nmbarrier.try_wait.parity.shared::cta.b64 p, [%1], %2, %3;\nselp.u32 %0, 1, 0, p;\n}"
                     : "=r"(ok) : "r"(bar), "r"(parity), "r"(EGC_HINT) : "memory");
    } while (!ok && ++spins < (1 << 16));
}
__device__ __forceinline__ void tma_2d(uint32_t dst, const CUtensorMap* map, int c0, int c1, uint32_t bar) {
    asm volatile("cp.async.bulk.tensor.2d.shared::cluster.global.mbarrier::complete_tx::bytes [%0], [%1, {%3, %4}], [%2];"
                 ::"r"(dst), "l"(map), "r"(bar), "r"(c0), "r"(c1) : "memory");
}
__device__ __forceinline__ void tma_3d(uint32_t dst, const CUtensorMap* map, int c0, int c1, int c2, uint32_t bar) {
    asm volatile("cp.async.bulk.tensor.3d.shared::cluster.global.mbarrier::complete_tx::bytes [%0], [%1, {%3, %4, %5}], [%2];"
                 ::"r"(dst), "l"(map), "r"(bar), "r"(c0), "r"(c1), "r"(c2) : "memory");
}
__device__ __forceinline__ void cp_async16(uint32_t dst, const void* src) {
    asm volatile("cp.async.cg.shared.global [%0], [%1], 16;" ::"r"(dst), "l"(src) : "memory");
}
__device__ __forceinline__ void cp_async16_if(bool p, uint32_t dst, const void* src) {
    asm volatile("{\n.reg .pred p;\nsetp.ne.u32 p, %2, 0;\n@p cp.async.cg.shared.global [%0], [%1], 16;\n}" ::"r"(dst), "l"(src), "r"((uint32_t)p) : "memory");
}
__device__ __forceinline__ void sts32_if(bool p, uint32_t a, uint32_t v) {
    asm volatile("{\n.reg .pred p;\nsetp.ne.u32 p, %2, 0;\n@p st.shared.u32 [%0], %1;\n}" ::"r"(a), "r"(v), "r"((uint32_t)p) : "memory");
}
__device__ __forceinline__ void sts16_if(bool p, uint32_t a, uint32_t v) {
    asm volatile("{\n.reg .pred p;\nsetp.ne.u32 p, %2, 0;\n@p st.shared.u16 [%0], %1;\n}" ::"r"(a), "h"((uint16_t)v), "r"((uint32_t)p) : "memory");
}
__device__ __forceinline__ void sts8_if(bool p, uint32_t a, uint32_t v) {
    asm volatile("{\n.reg .pred p;\nsetp.ne.u32 p, %2, 0;\n@p st.shared.u8 [%0], %1;\n}" ::"r"(a), "r"(v), "r"((uint32_t)p) : "memory");
}
__device__ __forceinline__ void cp_async_wait_all() { asm volatile("cp.async.wait_all;" ::: "memory"); }

__device__ __forceinline__ uint32_t lds32(uint32_t a) { uint32_t v; asm volatile("ld.shared.u32 %0, [%1];" : "=r"(v) : "r"(a)); return v; }
__device__ __forceinline__ uint2 lds64(uint32_t a) { uint2 v; asm volatile("ld.shared.v2.u32 {%0,%1}, [%2];" : "=r"(v.x), "=r"(v.y) : "r"(a)); return v; }
__device__ __forceinline__ uint4 lds128(uint32_t a) {
    uint4 v; asm volatile("ld.shared.v4.u32 {%0,%1,%2,%3}, [%4];" : "=r"(v.x), "=r"(v.y), "=r"(v.z), "=r"(v.w) : "r"(a)); return v;
}
__device__ __forceinline__ void sts16(uint32_t a, uint32_t v) { asm volatile("st.shared.u16 [%0], %1;" ::"r"(a), "h"((uint16_t)v) : "memory"); }
__device__ __forceinline__ void sts32(uint32_t a, uint32_t v) { asm volatile("st.shared.u32 [%0], %1;" ::"r"(a), "r"(v) : "memory"); }
__device__ __forceinline__ void sts128(uint32_t a, uint4 v) {
    asm volatile("st.shared.v4.u32 [%0], {%1,%2,%3,%4};" ::"r"(a), "r"(v.x), "r"(v.y), "r"(v.z), "r"(v.w) : "memory");
}
__device__ __forceinline__ uint32_t pack_bf16(float lo, float hi) {
    uint32_t d; asm("cvt.rn.bf16x2.f32 %0, %1, %2;" : "=r"(d) : "f"(hi), "f"(lo)); return d;
}
__device__ __forceinline__ uint32_t seteq_bf16x2(uint32_t a, uint32_t b) {
    uint32_t d; asm("set.eq.bf16x2.bf16x2 %0, %1, %2;" : "=r"(d) : "r"(a), "r"(b)); return d;
}
__device__ __forceinline__ float tanh_approx(float x) { float y; asm("tanh.approx.f32 %0, %1;" : "=f"(y) : "f"(x)); return y; }
__device__ __forceinline__ uint32_t bf16_bits_of_int(int v) { return __float_as_uint((float)v) >> 16; }

__device__ __forceinline__ void mma_bf16(float (&d)[4], uint32_t a0, uint32_t a1, uint32_t a2, uint32_t a3,
                                         uint32_t b0, uint32_t b1, float c0, float c1, float c2, float c3) {
    asm("mma.sync.aligned.m16n8k16.row.col.f32.bf16.bf16.f32 {%0,%1,%2,%3}, {%4,%5,%6,%7}, {%8,%9}, {%10,%11,%12,%13};"
        : "=f"(d[0]), "=f"(d[1]), "=f"(d[2]), "=f"(d[3])
        : "r"(a0), "r"(a1), "r"(a2), "r"(a3), "r"(b0), "r"(b1), "f"(c0), "f"(c1), "f"(c2), "f"(c3));
}

__device__ __forceinline__ void mma_bf16_k8(float (&d)[4], uint32_t a0, uint32_t a1, uint32_t b0) {
    asm("mma.sync.aligned.m16n8k8.row.col.f32.bf16.bf16.f32 {%0,%1,%2,%3}, {%4,%5}, {%6}, {%0,%1,%2,%3};"
        : "+f"(d[0]), "+f"(d[1]), "+f"(d[2]), "+f"(d[3]) : "r"(a0), "r"(a1), "r"(b0));
}

__device__ __forceinline__ void wgmma_n80(float (&d)[40], uint64_t da, uint64_t db, int scale_d) {
    asm volatile(
        "{\n.reg .pred p;\nsetp.ne.b32 p, %42, 0;\n"
        "wgmma.mma_async.sync.aligned.m64n80k16.f32.bf16.bf16 "
        "{%0,%1,%2,%3,%4,%5,%6,%7,%8,%9,%10,%11,%12,%13,%14,%15,%16,%17,%18,%19,"
        "%20,%21,%22,%23,%24,%25,%26,%27,%28,%29,%30,%31,%32,%33,%34,%35,%36,%37,%38,%39}, "
        "%40, %41, p, 1, 1, 1, 0;\n}"
        : "+f"(d[0]), "+f"(d[1]), "+f"(d[2]), "+f"(d[3]), "+f"(d[4]), "+f"(d[5]), "+f"(d[6]), "+f"(d[7]),
          "+f"(d[8]), "+f"(d[9]), "+f"(d[10]), "+f"(d[11]), "+f"(d[12]), "+f"(d[13]), "+f"(d[14]), "+f"(d[15]),
          "+f"(d[16]), "+f"(d[17]), "+f"(d[18]), "+f"(d[19]), "+f"(d[20]), "+f"(d[21]), "+f"(d[22]), "+f"(d[23]),
          "+f"(d[24]), "+f"(d[25]), "+f"(d[26]), "+f"(d[27]), "+f"(d[28]), "+f"(d[29]), "+f"(d[30]), "+f"(d[31]),
          "+f"(d[32]), "+f"(d[33]), "+f"(d[34]), "+f"(d[35]), "+f"(d[36]), "+f"(d[37]), "+f"(d[38]), "+f"(d[39])
        : "l"(da), "l"(db), "r"(scale_d));
}
__device__ __forceinline__ void wgmma_fence() { asm volatile("wgmma.fence.sync.aligned;" ::: "memory"); }
__device__ __forceinline__ void wgmma_commit() { asm volatile("wgmma.commit_group.sync.aligned;" ::: "memory"); }
template <int N> __device__ __forceinline__ void wgmma_wait() { asm volatile("wgmma.wait_group.sync.aligned %0;" ::"n"(N) : "memory"); }

__device__ __forceinline__ uint64_t smem_desc(uint32_t addr) {
    return (uint64_t)((addr & 0x3FFFF) >> 4) | ((uint64_t)1 << 16) | ((uint64_t)64 << 32) | ((uint64_t)1 << 62);
}

__device__ __forceinline__ void grid_wait(const unsigned int* ctr, unsigned int target) {
    unsigned int v;
    int spins = 0;
    do {
        asm volatile("ld.acquire.gpu.global.u32 %0, [%1];" : "=r"(v) : "l"(ctr) : "memory");
    } while ((int)(v - target) < 0 && ++spins < (1 << 21));
}

constexpr int GCNT = MISC_OFF + 64;

__device__ __forceinline__ uint32_t bin_rank(uint32_t sb, uint32_t w) {
    uint32_t rank;
    asm volatile("{\n.reg .pred p;\nsetp.lt.u32 p, %1, %3;\nmov.u32 %0, 0xFFFF;\n@p atom.shared.add.u32 %0, [%2], 1;\n}"
                 : "=r"(rank) : "r"(w >> 24), "r"(sb + GCNT + ((w >> 25) & 0x3C)), "n"(TILE) : "memory");
    return rank;
}
__device__ __forceinline__ void bin_store(uint32_t sb, uint32_t w, uint32_t rank, uint32_t row) {
    const uint32_t idx = (w >> 27) * CAPG + rank;
    sts32_if(rank < CAPG, sb + EL_OFF + idx * 4, w);
    sts8_if(rank < CAPG, sb + ER_OFF + idx, row);
}
__device__ __forceinline__ bool bar_or(int id, int n, bool v) {
    uint32_t r;
    asm volatile("{\n.reg .pred p, q;\nsetp.ne.u32 q, %3, 0;\nbarrier.cta.red.or.pred p, %1, %2, q;\nselp.u32 %0, 1, 0, p;\n}"
                 : "=r"(r) : "r"(id), "r"(n), "r"((uint32_t)v) : "memory");
    return r;
}

__device__ __forceinline__ int layout_list(uint32_t sb, int t, int last, int expanded) {
    int tot[10];
    {
        const uint4 a = lds128(sb + GCNT), b = lds128(sb + GCNT + 16);
        const uint2 c = lds64(sb + GCNT + 32);
        tot[0] = a.x; tot[1] = a.y; tot[2] = a.z; tot[3] = a.w; tot[4] = b.x; tot[5] = b.y; tot[6] = b.z; tot[7] = b.w;
        tot[8] = c.x; tot[9] = c.y;
    }
    int run = 0, myend = 0, gap = 0, tab = 0, mx = 0;
#pragma unroll
    for (int g = 0; g < 10; g++) {
        const int ge = run + ((tot[g] + 15) & ~15);
        const int off = t * 16 - run;
        if (off >= 0 && t * 16 < ge) tab = ((g * CAPG + off) << 16) | (tot[g] - off);
        if (g == t) myend = ge;
        if (g == 4) gap = ge;
        mx = max(mx, tot[g]);
        run = ge + (g == 4 ? 16 : 0);
    }
    if (mx > CAPG || run > CAP_STEPS * 16) return -1;
    if (t < CAP_STEPS) sts32(sb + CNT_OFF + t * 4, tab);
    if (t < 16) sts32(sb + MR_OFF + (run >> 4) * 128 + (t >> 1) * 16 + (t & 1) * 4, 0xFFFFFFFFu);
    if (t < 10) sts32(sb + MISC_OFF + t * 4, myend >> 4);
    if (t == 10) sts32(sb + MISC_OFF + 40, (gap >> 4) + 1);
    if (t == 11) sts32(sb + MISC_OFF + 44, last);
    if (t == 12) sts32(sb + MISC_OFF + 48, expanded ? -1 : run);
    return run;
}

__device__ __forceinline__ void expand_meta(uint32_t sb, int t, int run) {
#pragma unroll 2
    for (int pos = t; pos < run; pos += N_AUX) {
        const uint32_t tb = lds32(sb + CNT_OFF + (pos >> 4) * 4);
        const int k = pos & 15, st16 = pos & ~15;
        const bool v = k < (int)(tb & 0xFFFF);
        const uint32_t idx = v ? (tb >> 16) + k : 0;
        const uint32_t w = lds32(sb + EL_OFF + idx * 4);
        uint32_t row;
        asm volatile("ld.shared.u8 %0, [%1];" : "=r"(row) : "r"(sb + ER_OFF + idx));
        const uint32_t se = w & 0xFFFFFF, sn = se / EPC;
        const uint32_t dbf = v ? bf16_bits_of_int((w >> 24) & 7) : DBF_INV;
        const uint32_t mr = sb + MR_OFF + st16 * 8 + (k & 7) * 16 + (k >> 3) * 4;
        sts32(mr, v ? sn : 0xFFFFFFFFu);
        sts32(mr + 8, dbf * 0x10001u);
        sts16(sb + MQ_OFF + (st16 + ((k & 7) >> 1) * 4 + (k & 1) + 2 * (k >> 3)) * 2, dbf);
        sts32(sb + CAND_OFF + pos * 4, v ? (row - sn) * EPC + se : 0xFFFFFFFFu);
    }
}

template <int NTH>
__device__ __forceinline__ void gather_attr(uint32_t sb, int t, int run, const __nv_bfloat16* __restrict__ e_attr) {
    const int h = t & 1;
#pragma unroll 2
    for (int pos = t >> 1; pos < run; pos += NTH / 2) {
        const uint32_t e = lds32(sb + CAND_OFF + pos * 4);
        const bool v = e != 0xFFFFFFFFu;
        asm volatile("cp.async.cg.shared.global [%0], [%1], 16, %2;"
                     ::"r"(sb + EATTR_OFF + pos * 32 + ((h ^ ((pos >> 2) & 1)) << 4)),
                       "l"((const char*)e_attr + (v ? (size_t)e * 32 + h * 16 : 0)), "r"(v ? 16 : 0) : "memory");
    }
    if (t == 0) PROF2(113);
    cp_async_wait_all();
    if (t == 0) PROF2(114);
}

struct Params {
    const __nv_bfloat16* e_attr;
    const int* src;
    const int* dst;
    const __nv_bfloat16* g_w;
    const __nv_bfloat16* v_w;
    const __nv_bfloat16* u_w;
    __nv_bfloat16* out;
    uint4* tab;
    uint4* slots;
    unsigned int* bar;
    int zero;
};

__global__ void __launch_bounds__(NTHREADS, 1)
egc_kernel(const __grid_constant__ CUtensorMap tm_x, const __grid_constant__ CUtensorMap tm_g,
           const __grid_constant__ CUtensorMap tm_v, const __grid_constant__ CUtensorMap tm_u,
           const __grid_constant__ CUtensorMap tm_t, const __grid_constant__ Params P) {
    extern __shared__ __align__(1024) unsigned char smem_raw[];
    const uint32_t sb = (uint32_t)__cvta_generic_to_shared(smem_raw);
    if (sb & 1023u) __trap();
    const int tid = threadIdx.x, warp = tid >> 5, lane = tid & 31;
    const int tile = blockIdx.x;
    const uint32_t bar_full = sb + BAR_OFF, bar_empty = bar_full + 8 * NST, bar_x = bar_empty + 8 * NST, bar_idx = bar_x + 32;
    const __nv_bfloat16* __restrict__ e_attr = P.e_attr;

    int4 dv, sv;
    if (warp < 16) {
        if (tid < EPC / 4) {
            asm volatile("ld.global.nc.v4.s32 {%0,%1,%2,%3}, [%4];" : "=r"(dv.x), "=r"(dv.y), "=r"(dv.z), "=r"(dv.w)
                         : "l"((const int4*)P.dst + tile * (EPC / 4) + tid));
            asm volatile("ld.global.nc.v4.s32 {%0,%1,%2,%3}, [%4];" : "=r"(sv.x), "=r"(sv.y), "=r"(sv.z), "=r"(sv.w)
                         : "l"((const int4*)P.src + tile * (EPC / 4) + tid));
        }
        sts128(sb + CAND_OFF + tid * 16, make_uint4(REC_INV, REC_INV, REC_INV, REC_INV));
        sts128(sb + CAND_OFF + (tid + 512) * 16, make_uint4(REC_INV, REC_INV, REC_INV, REC_INV));
        if (tid < 128) sts32(sb + CNT_OFF + tid * 4, 0);
        if (tid == 0) { PROF(0); PROF2(64); }
    } else if (warp < 20) {
        if (tid < N_MAIN + 16) sts32(sb + GCNT + (tid - N_MAIN) * 4, 0);
    } else if (tid == 640) {
        asm volatile("prefetch.tensormap [%0];" ::"l"(&tm_g) : "memory");
#pragma unroll
        for (int s = 0; s < NST; s++) {
            mbar_init(bar_full + 8 * s, 1);
            mbar_init(bar_empty + 8 * s, 16);
        }
        asm volatile("fence.mbarrier_init.release.cluster;" ::: "memory");
#pragma unroll 1
        for (int it = 0; it < NST; it++) {
            mbar_expect_tx(bar_full + 8 * it, 32768);
            tma_3d(sb + RING_OFF + it * 32768, &tm_g, 0, 256 + it * 64, 0, bar_full + 8 * it);
        }
    } else if (tid == 704) {
        asm volatile("prefetch.tensormap [%0];" ::"l"(&tm_x) : "memory");
#pragma unroll
        for (int s = 0; s < 4; s++) mbar_init(bar_x + 8 * s, 1);
        mbar_init(bar_idx, EPC / 128);
        asm volatile("fence.mbarrier_init.release.cluster;" ::: "memory");
#pragma unroll 1
        for (int c = 0; c < X_EARLY; c++) {
            mbar_expect_tx(bar_x + 8 * c, 10240);
            tma_2d(sb + X_OFF + c * 10240, &tm_x, c * 64, tile * TILE, bar_x + 8 * c);
        }
    } else if (tid == 672) {
        asm volatile("prefetch.tensormap [%0];" ::"l"(&tm_v) : "memory");
        asm volatile("prefetch.tensormap [%0];" ::"l"(&tm_u) : "memory");
        asm volatile("prefetch.tensormap [%0];" ::"l"(&tm_t) : "memory");
        const int go = tile * 2176, vo = tile * 1056;
        const int gn = min(2176, 528 * 512 - go), vn = min(1056, 256 * 512 - vo);
        if (gn > 0) asm volatile("cp.async.bulk.prefetch.L2.global [%0], %1;" ::"l"((const char*)P.g_w + go), "r"(gn) : "memory");
        if (vn > 0) {
            asm volatile("cp.async.bulk.prefetch.L2.global [%0], %1;" ::"l"((const char*)P.v_w + vo), "r"(vn) : "memory");
            asm volatile("cp.async.bulk.prefetch.L2.global [%0], %1;" ::"l"((const char*)P.u_w + vo), "r"(vn) : "memory");
        }
    }
    __syncthreads();

    if (warp >= 20) {
        asm volatile("setmaxnreg.dec.sync.aligned.u32 24;");
        if (tid == 640) {
            int st = 0, par = 0;
#pragma unroll 1
            for (int it = NST; it < NIT; it++) {
                const int p = it >> 2;
                const CUtensorMap* m = (p == 1) ? &tm_v : (p == 3) ? &tm_u : &tm_g;
                const int row = ((p == 0) ? 256 : 0) + (it & 3) * 64;
                mbar_wait(bar_empty + 8 * st, par);
                mbar_expect_tx(bar_full + 8 * st, 32768);
                tma_3d(sb + RING_OFF + st * 32768, m, 0, row, 0, bar_full + 8 * st);
                if (++st == NST) { st = 0; par ^= 1; }
            }
        } else if (tid == 704) {
            if (X_EARLY < 4) mbar_wait(bar_idx, 0);
#pragma unroll 1
            for (int c = X_EARLY; c < 4; c++) {
                mbar_expect_tx(bar_x + 8 * c, 10240);
                tma_2d(sb + X_OFF + c * 10240, &tm_x, c * 64, tile * TILE, bar_x + 8 * c);
            }
        } else if (warp == 21) {
            mbar_wait(bar_x + 8 * 3, 0);
#pragma unroll 1
            for (int i = lane; i < EPC * 32 / 128; i += 32)
                asm volatile("prefetch.global.L2 [%0];" ::"l"((const char*)e_attr + (size_t)tile * EPC * 32 + i * 128) : "memory");
        } else if (warp == 23) {
#pragma unroll 1
            for (int wave = 0; wave < 2; wave++) {
                bar_sync(BAR_TABLE, N_MAIN + 32);
                if (lane == 0) {
#pragma unroll 1
                    for (int ds = 0; ds < 8; ds++)
                        asm volatile("cp.async.bulk.tensor.2d.global.shared::cta.bulk_group [%0, {%2, %3}], [%1];"
                                     ::"l"(&tm_t), "r"(sb + EATTR_OFF + ds * 5120), "r"(ds * 64), "r"(tile * TILE + wave * 40) : "memory");
                    asm volatile("cp.async.bulk.commit_group;" ::: "memory");
                    asm volatile("cp.async.bulk.wait_group.read 0;" ::: "memory");
                }
                __syncwarp();
                bar_arrive(BAR_STG, N_MAIN + 32);
            }
            if (lane == 0) {
                asm volatile("cp.async.bulk.wait_group 0;" ::: "memory");
                asm volatile("fence.proxy.async;" ::: "memory");
                PROF(6);
                __threadfence();
                const unsigned int old = atomicAdd(P.bar, 1u);
                grid_wait(P.bar, (old / NT + 1u) * NT);
                PROF(4);
            }
            __syncwarp();
            bar_arrive(BAR_GO, N_MAIN + 32);
        }
    } else if (warp >= 16) {
        asm volatile("setmaxnreg.dec.sync.aligned.u32 40;");
        const int t = tid - N_MAIN;
        bar_sync(BAR_S1, N_MAIN + N_AUX);
        if (t == 0) {
            PROF(1);
            __threadfence();
            const unsigned int old = atomicAdd(P.bar + 32, 1u);
            grid_wait(P.bar + 32, (old / NT + 1u) * NT);
            PROF(2); PROF2(99);
        }
        bar_sync(BAR_AUX, N_AUX);
        const uint32_t row = sb + CAND_OFF + t * 32;
#pragma unroll 1
        for (int j = 0; j < 8; j++) {
            const uint32_t a = row + (j >> 1) * 4096 + (j & 1) * 16;
            if (t < NT) cp_async16(a, P.slots + (size_t)(tile * 4 + (j >> 1)) * (NT * 2) + t * 2 + (j & 1));
            else sts128(a, make_uint4(REC_INV, REC_INV, REC_INV, REC_INV));
        }
        cp_async_wait_all();
        if (t == 0) PROF2(100);
        bool ovf = false;
#pragma unroll 1
        for (int j = 0; j < 4; j++) {
            const uint4 a = lds128(row + j * 4096), b = lds128(row + j * 4096 + 16);
            if (j >= 2 && !__any_sync(0xffffffffu, rec_dl(a.x) != 127)) break;
            const uint32_t rec[8] = {a.x, a.y, a.z, a.w, b.x, b.y, b.z, b.w};
            uint32_t rank[8];
#pragma unroll
            for (int i = 0; i < 8; i++) rank[i] = bin_rank(sb, rec[i]);
#pragma unroll
            for (int i = 0; i < 8; i++) bin_store(sb, rec[i], rank[i], t);
            ovf |= rec_dl(b.w) == 126;
        }
        if (t == 0) PROF2(101);
        ovf = bar_or(BAR_AUX, N_AUX, ovf);
        if (t == 0) { PROF(11); PROF2(105); }
        int run = ovf ? -1 : layout_list(sb, t, 1, 0);
        if (run >= 0) {
            bar_sync(BAR_AUX, N_AUX);
            if (t == 0) PROF2(107);
            expand_meta(sb, t, run);
            if (t == 0) { PROF(3); PROF2(108); }
            bar_arrive(BAR_READY, N_MAIN + N_AUX);
        } else {
            bar_sync(BAR_AUX, N_AUX);
            if (t < 16) sts32(sb + GCNT + t * 4, 0);
            bar_sync(BAR_AUX, N_AUX);
            bool first = true;
#pragma unroll 1
            for (int w0 = 0; w0 < NT * EPC; w0 += 128) {
                const int e = w0 + t, d = __ldg(P.dst + e), b = (unsigned)d / TILE;
                uint32_t w = REC_INV;
                const int c = (unsigned)e / EPC;
                if (b == tile) w = ((uint32_t)(d - b * TILE) << 24) | (__ldg(P.src + e) * EPC + (e - c * EPC));
                bin_store(sb, w, bin_rank(sb, w), c);
                bar_sync(BAR_AUX, N_AUX);
                int mx = 0, sum = 0;
#pragma unroll 1
                for (int g = 0; g < 10; g++) { const int v = lds32(sb + GCNT + g * 4); mx = max(mx, v); sum += v; }
                const bool fin = w0 + 128 >= NT * EPC;
                const bool flush = fin || mx > CAPG - 128 || sum > CAP_STEPS * 16 - 16 - 150 - 128;
                bar_sync(BAR_AUX, N_AUX);
                if (flush) {
                    if (first) bar_sync(BAR_XFREE, N_MAIN + N_AUX);
                    else bar_sync(BAR_CONSUMED, N_MAIN + N_AUX);
                    first = false;
                    run = layout_list(sb, t, fin, 1);
                    bar_sync(BAR_AUX, N_AUX);
                    expand_meta(sb, t, run);
                    bar_sync(BAR_AUX, N_AUX);
                    gather_attr<N_AUX>(sb, t, run, e_attr);
                    bar_arrive(BAR_READY, N_MAIN + N_AUX);
                    bar_sync(BAR_AUX, N_AUX);
                    if (t < 16) sts32(sb + GCNT + t * 4, 0);
                    bar_sync(BAR_AUX, N_AUX);
                }
            }
        }
    } else {
        asm volatile("setmaxnreg.inc.sync.aligned.u32 104;");
        const int wg = warp >> 2;
        const int r = lane >> 2, q = lane & 3;
        if (tid < EPC / 4) {
            const int dd[4] = {dv.x, dv.y, dv.z, dv.w};
            const int ss[4] = {sv.x, sv.y, sv.z, sv.w};
            uint32_t rank[4];
            int bb[4];
#pragma unroll
            for (int i = 0; i < 4; i++) {
                bb[i] = (unsigned)dd[i] / TILE;
                asm volatile("atom.shared.add.u32 %0, [%1], 1;" : "=r"(rank[i]) : "r"(sb + CNT_OFF + bb[i] * 4) : "memory");
            }
#pragma unroll
            for (int i = 0; i < 4; i++) {
                const uint32_t rec = ((uint32_t)(dd[i] - bb[i] * TILE) << 24) | (ss[i] * EPC + tid * 4 + i);
                sts32(sb + CAND_OFF + bb[i] * 128 + (min(rank[i], 31u) << 2), rank[i] < 31 ? rec : REC_OVF);
            }
            __syncwarp();
            if (lane == 0) mbar_arrive(bar_idx);
        }
        bar_sync(BAR_MAIN, N_MAIN);
        if (tid == 0) PROF(14);
#pragma unroll
        for (int j = 0; j < 2; j++) {
            const int idx = tid + 512 * j;
            if (idx < NT * 8) {
                const uint4 v = lds128(sb + CAND_OFF + idx * 16);
                __stcg(P.slots + (size_t)((idx >> 3) * 4 + ((idx >> 1) & 3)) * (NT * 2) + tile * 2 + (idx & 1), v);
            }
        }
        bar_arrive(BAR_S1, N_MAIN + N_AUX);

        float d[40];
        uint32_t pB[20], pV[20], xa[20];
        const uint64_t da0 = smem_desc(sb + RING_OFF + wg * 8192), db0 = smem_desc(sb + X_OFF);
        int st = 0, par = 0;
        const bool odd = r & 1;

        auto stage = [&](const int p, const int c) {
            if (p == 0) mbar_wait(bar_x + 8 * c, 0);
            if (p == 0 && c == 0 && tid == 0) PROF(5);
            mbar_wait(bar_full + 8 * st, par);
            if (tid == 0) PROF2(p * 4 + c);
            wgmma_fence();
            const uint64_t da = da0 + st * 2048, db = db0 + c * 640;
            wgmma_n80(d, da, db, c != 0);
            wgmma_n80(d, da + 128, db + 2, 1);
            wgmma_n80(d, da + 256, db + 4, 1);
            wgmma_n80(d, da + 384, db + 6, 1);
            wgmma_commit();
        };
        auto release_prev = [&](const int it) {
            if (lane == 0 && it + NST < NIT) mbar_arrive(bar_empty + 8 * (st == 0 ? NST - 1 : st - 1));
        };

        auto stage_table = [&](const int wave) {
            const uint32_t base = sb + EATTR_OFF + (warp >> 1) * 5120 + (r & 1) * 8 + 2 * q * 128;
            const uint32_t ch = (warp & 1) * 4 + (r >> 1);
#pragma unroll
            for (int jj = 0; jj < 10; jj++) {
                const int j = wave * 10 + jj;
                const uint32_t rv = __shfl_xor_sync(0xffffffffu, odd ? pB[j] : pV[j], 4);
                asm volatile("st.shared.v2.u32 [%0], {%1, %2};"
                             ::"r"(base + ((jj >> 1) * 8 + (jj & 1)) * 128 + ((ch ^ (2 * q + (jj & 1))) << 4)),
                               "r"(odd ? rv : pB[j]), "r"(odd ? pV[j] : rv) : "memory");
            }
            asm volatile("fence.proxy.async.shared::cta;" ::: "memory");
            bar_arrive(BAR_TABLE, N_MAIN + 32);
        };
        uint16_t craw[2][8];
#pragma unroll
        for (int p = 0; p < 4; p++) {
            if (p == 2) {
#pragma unroll
                for (int c = 0; c < 4; c++) {
                    stage(p, c);
                    if (c == 0) stage_table(0);
                    if (c == 3) { bar_sync(BAR_STG, N_MAIN + 32); stage_table(1); }
                    if (c > 0) { wgmma_wait<1>(); release_prev(p * 4 + c - 1); }
                    if (++st == NST) { st = 0; par ^= 1; }
                }
            } else {
#pragma unroll 1
                for (int c = 0; c < 4; c++) {
                    stage(p, c);
                    if (c > 0) { wgmma_wait<1>(); release_prev(p * 4 + c - 1); }
                    if (++st == NST) { st = 0; par ^= 1; }
                }
            }
            if (p == 3) {
#pragma unroll
                for (int c = 0; c < 2; c++) {
                    const __nv_bfloat16* cw = P.g_w + 512 * DD + (warp & 7) * 32 + c * 16;
#pragma unroll
                    for (int i = 0; i < 8; i++) {
                        const int ch = r + ((i >> 1) & 1) * 8, k = 2 * q + (i >> 2) * 8 + (i & 1);
                        asm volatile("ld.global.nc.u16 %0, [%1];" : "=h"(craw[c][i]) : "l"(cw + k * DD + ch));
                    }
                }
            }
            wgmma_wait<0>();
            release_prev(p * 4 + 3);
            if (p == 0) {
#pragma unroll
                for (int j = 0; j < 10; j++) {
                    pB[2 * j] = pack_bf16(0.5f * d[4 * j], 0.5f * d[4 * j + 2]);
                    pB[2 * j + 1] = pack_bf16(0.5f * d[4 * j + 1], 0.5f * d[4 * j + 3]);
                }
            } else if (p == 1) {
#pragma unroll
                for (int j = 0; j < 10; j++) {
                    pV[2 * j] = pack_bf16(0.5f * d[4 * j], 0.5f * d[4 * j + 2]);
                    pV[2 * j + 1] = pack_bf16(0.5f * d[4 * j + 1], 0.5f * d[4 * j + 3]);
                }
            } else if (p == 2) {
#pragma unroll
                for (int j = 0; j < 20; j++) xa[j] = pack_bf16(0.5f * d[2 * j], 0.5f * d[2 * j + 1]);
            }
        }
        if (tid == 0) { PROF(7); PROF2(109); }

        bar_sync(BAR_MAIN, N_MAIN);
#pragma unroll
        for (int j = 0; j < 10; j++) {
            sts128(sb + PARK_ACC + (warp * 10 + j) * 512 + lane * 16,
                   make_uint4(__float_as_uint(d[4 * j]), __float_as_uint(d[4 * j + 1]), __float_as_uint(d[4 * j + 2]), __float_as_uint(d[4 * j + 3])));
            asm volatile("st.shared.v2.u32 [%0], {%1, %2};" ::"r"(sb + PARK_XA + (warp * 10 + j) * 256 + lane * 8), "r"(xa[2 * j]), "r"(xa[2 * j + 1]) : "memory");
        }
        bar_sync(BAR_MAIN, N_MAIN);

        {
            const int ds = warp & 7, set = warp >> 3;
            uint32_t cf[2][4];
#pragma unroll
            for (int c = 0; c < 2; c++)
#pragma unroll
                for (int i = 0; i < 4; i++)
                    cf[c][i] = pack_bf16(0.5f * __uint_as_float((uint32_t)craw[c][2 * i] << 16), 0.5f * __uint_as_float((uint32_t)craw[c][2 * i + 1] << 16));
            const uint32_t cA = bf16_bits_of_int(2 * q) | (bf16_bits_of_int(2 * q + 1) << 16);
            const uint32_t cB = bf16_bits_of_int(r) * 0x10001u;
            const uint32_t ia0 = (r == 2 * q) ? 0x00003F80u : 0u, ia1 = ia0 << 16;
            const uint32_t ia2 = (r == 2 * q + 1) ? 0x00003F80u : 0u, ia3 = ia2 << 16;
            const char* tabl = (const char*)P.tab + ds * 128 + q * 16;
            const int ek = (lane >> 4) * 8 + (lane & 7);
            const uint32_t ea_l = sb + EATTR_OFF + ek * 32 + ((((lane >> 3) & 1) ^ ((ek >> 2) & 1)) << 4);
            const uint32_t mr_l = sb + MR_OFF + r * 16;
            const uint32_t mq_l = sb + MQ_OFF + q * 8;
            const uint32_t bounce = sb + CAND_OFF + warp * 512;
            const uint32_t pk_acc = sb + PARK_ACC + (ds * 20 + set * 5) * 512 + lane * 16;
            const uint32_t pk_xa = sb + PARK_XA + (ds * 20 + set * 5) * 256 + lane * 8;
            const uint32_t zero = (uint32_t)P.zero;

            uint4 bx[4], by[4];
#pragma unroll
            for (int i = 0; i < 4; i++) { bx[i] = make_uint4(0, 0, 0, 0); by[i] = make_uint4(0, 0, 0, 0); }

            auto gather2 = [&](uint4& b0, uint4& b1, uint32_t w) {
                asm volatile("{\n.reg .pred p;\n.reg .b64 a;\nsetp.ge.s32 p, %8, 0;\nmad.wide.u32 a, %8, 1024, %9;\n"
                             "@p ld.global.cg.v4.u32 {%0,%1,%2,%3}, [a];\n@p ld.global.cg.v4.u32 {%4,%5,%6,%7}, [a+64];\n}"
                             : "+r"(b0.x), "+r"(b0.y), "+r"(b0.z), "+r"(b0.w), "+r"(b1.x), "+r"(b1.y), "+r"(b1.z), "+r"(b1.w)
                             : "r"(w), "l"(tabl));
            };

            if (tid == 0) PROF2(110);
            bar_sync(BAR_STG, N_MAIN + 32);
            if (tid == 0) PROF2(111);
            bar_arrive(BAR_XFREE, N_MAIN + N_AUX);
            bool go = false;
            for (;;) {
                bar_sync(BAR_READY, N_MAIN + N_AUX);
                if (tid == 0) PROF2(112);
                const int run = lds32(sb + MISC_OFF + 48);
                if (run >= 0) {
                    gather_attr<N_MAIN>(sb, tid, run, e_attr);
                    bar_sync(BAR_MAIN, N_MAIN);
                }
                if (tid == 0) PROF(15);
                if (!go) { bar_sync(BAR_GO, N_MAIN + 32); go = true; }
                if (tid == 0) { asm volatile("" ::: "memory"); PROF(8); PROF2(66); }
                const int last = lds32(sb + MISC_OFF + 44);
                int i = set ? (int)lds32(sb + MISC_OFF + 40) : 0;
                uint32_t pe = ea_l + i * 512, pr = mr_l + i * 128, pq = mq_l + i * 32;
                {
                    const uint2 w0 = lds64(pr);
                    gather2(bx[0], bx[1], w0.x);
                    gather2(bx[2], bx[3], w0.y);
                }
                uint2 wn = lds64(pr + 128);
                int ph = 0;
                for (int g = 0; g < 5; g++) {
                    const int gend = lds32(sb + MISC_OFF + (set * 5 + g) * 4);
                    float acc[2][4];
                    uint2 xf[2];
#pragma unroll
                    for (int c = 0; c < 2; c++) {
                        const uint4 a = lds128(pk_acc + (c * 10 + g) * 512);
                        acc[c][0] = __uint_as_float(a.x); acc[c][1] = __uint_as_float(a.y);
                        acc[c][2] = __uint_as_float(a.z); acc[c][3] = __uint_as_float(a.w);
                        xf[c] = lds64(pk_xa + (c * 10 + g) * 256);
                    }

                    auto step = [&](uint4 (&cur)[4], uint4 (&nxt)[4], const int k) {
                        const uint32_t dep = cur[0].x & zero;
                        gather2(nxt[0], nxt[1], wn.x | dep);
                        gather2(nxt[2], nxt[3], wn.y | dep);
                        wn = lds64(pr + (k + 2) * 128);
                        const uint2 dd = lds64(pr + k * 128 + 8);
                        const uint2 db = lds64(pq + k * 32);
                        uint32_t e0, e1, e2, e3;
                        asm volatile("ldmatrix.sync.aligned.m8n8.x4.shared.b16 {%0,%1,%2,%3}, [%4];"
                                     : "=r"(e0), "=r"(e1), "=r"(e2), "=r"(e3) : "r"(pe + k * 512));
                        const uint32_t sa0 = seteq_bf16x2(dd.x, cA), sa1 = seteq_bf16x2(dd.y, cA);
                        const uint32_t sb0 = seteq_bf16x2(db.x, cB), sb1 = seteq_bf16x2(db.y, cB);
#pragma unroll
                        for (int c = 0; c < 2; c++) {
                            float p0[4], p1[4], h0[4], h1[4];
                            mma_bf16(p0, cf[c][0], cf[c][1], cf[c][2], cf[c][3], e0, e1, 0.f, 0.f, 0.f, 0.f);
                            mma_bf16(p1, cf[c][0], cf[c][1], cf[c][2], cf[c][3], e2, e3, 0.f, 0.f, 0.f, 0.f);
                            mma_bf16_k8(p0, xf[c].x, xf[c].y, sa0);
                            mma_bf16_k8(p1, xf[c].x, xf[c].y, sa1);
                            mma_bf16(p0, ia0, ia1, ia2, ia3, cur[c].x, cur[c].y, p0[0], p0[1], p0[2], p0[3]);
                            mma_bf16(p1, ia0, ia1, ia2, ia3, cur[2 + c].x, cur[2 + c].y, p1[0], p1[1], p1[2], p1[3]);
                            mma_bf16(h0, ia0, ia1, ia2, ia3, cur[c].z, cur[c].w, 0.f, 0.f, 0.f, 0.f);
                            mma_bf16(h1, ia0, ia1, ia2, ia3, cur[2 + c].z, cur[2 + c].w, 0.f, 0.f, 0.f, 0.f);
                            float m0[4], m1[4];
#pragma unroll
                            for (int j = 0; j < 4; j++) {
                                m0[j] = fmaf(tanh_approx(p0[j]), h0[j], h0[j]);
                                m1[j] = fmaf(tanh_approx(p1[j]), h1[j], h1[j]);
                            }
                            mma_bf16(acc[c], pack_bf16(m0[0], m0[1]), pack_bf16(m0[2], m0[3]), pack_bf16(m1[0], m1[1]), pack_bf16(m1[2], m1[3]),
                                     sb0, sb1, acc[c][0], acc[c][1], acc[c][2], acc[c][3]);
                        }
                    };

                    int rem = gend - i;
                    i = gend;
                    while (rem > 0) {
                        if (ph == 0) {
                            step(bx, by, 0);
                            ph = 1;
                            if (--rem == 0) break;
                        }
                        step(by, bx, 1);
                        ph = 0; pe += 2 * 512; pr += 2 * 128; pq += 2 * 32; --rem;
                    }

                    if (last) {
                        uint32_t o[4];
#pragma unroll
                        for (int c = 0; c < 2; c++) {
                            float z[4];
#pragma unroll
                            for (int j = 0; j < 4; j++) z[j] = __fdividef(acc[c][j], 1.f + __expf(-acc[c][j]));
                            o[2 * c] = pack_bf16(z[0], z[1]);
                            o[2 * c + 1] = pack_bf16(z[2], z[3]);
                        }
                        asm volatile("stmatrix.sync.aligned.m8n8.x4.trans.shared.b16 [%0], {%1,%2,%3,%4};"
                                     ::"r"(bounce + (lane & 7) * 64 + (((lane >> 3) ^ ((lane >> 1) & 3)) << 4)),
                                       "r"(o[0]), "r"(o[1]), "r"(o[2]), "r"(o[3]) : "memory");
                        __syncwarp();
                        const int node = lane >> 2;
                        const uint4 v = lds128(bounce + node * 64 + ((q ^ ((node >> 1) & 3)) << 4));
                        *(uint4*)(P.out + (size_t)(tile * TILE + (set * 5 + g) * 8 + node) * DD + ds * 32 + q * 8) = v;
                        __syncwarp();
                    } else {
#pragma unroll
                        for (int c = 0; c < 2; c++)
                            sts128(pk_acc + (c * 10 + g) * 512, make_uint4(__float_as_uint(acc[c][0]), __float_as_uint(acc[c][1]),
                                                                           __float_as_uint(acc[c][2]), __float_as_uint(acc[c][3])));
                    }
                }
                if (last) break;
                bar_arrive(BAR_CONSUMED, N_MAIN + N_AUX);
            }
            if (tid == 0) { PROF(9); PROF2(65); }
        }
    }
}

typedef CUresult (*EncodeFn)(CUtensorMap*, CUtensorMapDataType, cuuint32_t, void*, const cuuint64_t*, const cuuint64_t*,
                             const cuuint32_t*, const cuuint32_t*, CUtensorMapInterleave, CUtensorMapSwizzle,
                             CUtensorMapL2promotion, CUtensorMapFloatOOBfill);

static void make_map(EncodeFn fn, CUtensorMap* m, const void* ptr, int rows, int box_rows) {
    cuuint64_t dims[2] = {(cuuint64_t)DD, (cuuint64_t)rows};
    cuuint64_t strides[1] = {(cuuint64_t)DD * 2};
    cuuint32_t box[2] = {64, (cuuint32_t)box_rows};
    cuuint32_t es[2] = {1, 1};
    fn(m, CU_TENSOR_MAP_DATA_TYPE_BFLOAT16, 2, const_cast<void*>(ptr), dims, strides, box, es, CU_TENSOR_MAP_INTERLEAVE_NONE,
       CU_TENSOR_MAP_SWIZZLE_128B, CU_TENSOR_MAP_L2_PROMOTION_L2_256B, CU_TENSOR_MAP_FLOAT_OOB_FILL_NONE);
}

static void make_tmap(EncodeFn fn, CUtensorMap* m, void* ptr) {
    cuuint64_t dims[2] = {512, (cuuint64_t)NN};
    cuuint64_t strides[1] = {1024};
    cuuint32_t box[2] = {64, 40};
    cuuint32_t es[2] = {1, 1};
    fn(m, CU_TENSOR_MAP_DATA_TYPE_BFLOAT16, 2, ptr, dims, strides, box, es, CU_TENSOR_MAP_INTERLEAVE_NONE,
       CU_TENSOR_MAP_SWIZZLE_128B, CU_TENSOR_MAP_L2_PROMOTION_NONE, CU_TENSOR_MAP_FLOAT_OOB_FILL_NONE);
}

static void make_wmap(EncodeFn fn, CUtensorMap* m, const void* ptr, int rows) {
    cuuint64_t dims[3] = {64, (cuuint64_t)rows, 4};
    cuuint64_t strides[2] = {(cuuint64_t)DD * 2, 128};
    cuuint32_t box[3] = {64, 64, 4};
    cuuint32_t es[3] = {1, 1, 1};
    fn(m, CU_TENSOR_MAP_DATA_TYPE_BFLOAT16, 3, const_cast<void*>(ptr), dims, strides, box, es, CU_TENSOR_MAP_INTERLEAVE_NONE,
       CU_TENSOR_MAP_SWIZZLE_128B, CU_TENSOR_MAP_L2_PROMOTION_L2_256B, CU_TENSOR_MAP_FLOAT_OOB_FILL_NONE);
}

}

extern "C" void kernel_launch(void* const* d_in, const int* in_sizes, int n_in, void* d_out, int out_size) {
    using namespace egc;
    (void)in_sizes; (void)n_in; (void)out_size;
    static EncodeFn encode = nullptr;
    static void *p_tab = nullptr, *p_slots = nullptr, *p_bar = nullptr;
    if (!encode) {
        void* fn = nullptr;
        cudaDriverEntryPointQueryResult qr;
        cudaGetDriverEntryPoint("cuTensorMapEncodeTiled", &fn, cudaEnableDefault, &qr);
        encode = (EncodeFn)fn;
        cudaFuncSetAttribute(egc_kernel, cudaFuncAttributeMaxDynamicSharedMemorySize, SMEM_BYTES);
        cudaGetSymbolAddress(&p_tab, g_tab);
        cudaGetSymbolAddress(&p_slots, g_slots);
        cudaGetSymbolAddress(&p_bar, g_bar);
    }
    const __nv_bfloat16* x = (const __nv_bfloat16*)d_in[0];
    Params P;
    P.e_attr = (const __nv_bfloat16*)d_in[1];
    P.src = (const int*)d_in[2];
    P.dst = (const int*)d_in[3];
    P.u_w = (const __nv_bfloat16*)d_in[4];
    P.v_w = (const __nv_bfloat16*)d_in[5];
    P.g_w = (const __nv_bfloat16*)d_in[6];
    P.out = (__nv_bfloat16*)d_out;
    P.tab = (uint4*)p_tab;
    P.slots = (uint4*)p_slots;
    P.bar = (unsigned int*)p_bar;
    P.zero = 0;
    CUtensorMap tx, tg, tv, tu, tt;
    make_tmap(encode, &tt, p_tab);
    make_map(encode, &tx, x, NN, TILE);
    make_wmap(encode, &tg, P.g_w, 2 * DD + 16);
    make_wmap(encode, &tv, P.v_w, DD);
    make_wmap(encode, &tu, P.u_w, DD);
    egc_kernel<<<NT, NTHREADS, SMEM_BYTES, cudaStreamPerThread>>>(tx, tg, tv, tu, tt, P);
}
```

```cpp
#include <cuda_runtime.h>
#include <cuda_bf16.h>
#include <cuda.h>
#include <stdint.h>

namespace egc {

constexpr int NN = 10000;
constexpr int DD = 256;
constexpr int TILE = 80;
constexpr int NT = 125;
constexpr int EPC = 1280;
constexpr int NST = 3;
constexpr int NIT = 16;
#define EGC_HINT 20000
#define EGC_WAVE2 10
#define EGC_PACING 0
#define EGC_PACE_N 3
#define EGC_PACE_0 4
#define EGC_PACE_F 15
#define EGC_NAVG 44
#define EGC_YIELD 0
#define EGC_STQ 1
#define EGC_X_EARLY 2
constexpr int X_EARLY = EGC_X_EARLY;
constexpr int CAP_STEPS = 98;

constexpr int N_MAIN = 512, N_AUX = 128;
constexpr int NTHREADS = N_MAIN + N_AUX + 128;

constexpr int X_OFF = 0;
constexpr int RING_OFF = 40960;
constexpr int PARK_ACC = 0;
constexpr int CT_OFF = RING_OFF + 32768;
constexpr int YB_OFF = 122880;
constexpr int PARK_XA = 81920;
constexpr int EATTR_OFF = RING_OFF + NST * 32768;
constexpr int CAND_OFF = EATTR_OFF + CAP_STEPS * 512;
constexpr int MR_OFF = CAND_OFF + 16384;
constexpr int MQ_OFF = MR_OFF + (CAP_STEPS + 2) * 128;
constexpr int CAPG = 192;
constexpr int EL_OFF = MQ_OFF + CAP_STEPS * 32;
constexpr int ER_OFF = EL_OFF + 10 * CAPG * 4;
constexpr int CNT_OFF = ER_OFF + 10 * CAPG;
constexpr int MISC_OFF = CNT_OFF + 512;
constexpr int BAR_OFF = MISC_OFF + 128;
constexpr int SMEM_BYTES = BAR_OFF + 128;
static_assert(PARK_XA + 40960 <= EATTR_OFF, "parking area must fit in x + ring");
static_assert(SMEM_BYTES <= 232448, "too much shared memory");

constexpr uint32_t REC_INV = 0x7FFFFFFFu, REC_OVF = 0x7E000000u;
__device__ __forceinline__ uint32_t rec_dl(uint32_t w) { return (w >> 24) & 127; }
constexpr uint32_t DBF_INV = 0x4380u;

constexpr int BAR_AUX = 1, BAR_MAIN = 2, BAR_READY = 3, BAR_CONSUMED = 4, BAR_TABLE = 5, BAR_GO = 6, BAR_S1 = 7, BAR_STG = 8, BAR_XFREE = 9;

__device__ uint4 g_tab[(size_t)NN * 64];
__device__ uint4 g_slots[(size_t)NT * NT * 8];
__device__ unsigned int g_bar[64];
#define PROF(i) do { } while (0)
#define PROF2(i) do { } while (0)

__device__ __forceinline__ void bar_sync(int id, int n) { asm volatile("bar.sync %0, %1;" ::"r"(id), "r"(n) : "memory"); }
__device__ __forceinline__ void bar_arrive(int id, int n) { asm volatile("bar.arrive %0, %1;" ::"r"(id), "r"(n) : "memory"); }

__device__ __forceinline__ void mbar_init(uint32_t bar, uint32_t cnt) {
    asm volatile("mbarrier.init.shared::cta.b64 [%0], %1;" ::"r"(bar), "r"(cnt) : "memory");
}
__device__ __forceinline__ void mbar_expect_tx(uint32_t bar, uint32_t bytes) {
    asm volatile("mbarrier.arrive.expect_tx.shared::cta.b64 _, [%0], %1;" ::"r"(bar), "r"(bytes) : "memory");
}
__device__ __forceinline__ void mbar_arrive(uint32_t bar) {
    asm volatile("mbarrier.arrive.shared::cta.b64 _, [%0];" ::"r"(bar) : "memory");
}
__device__ __forceinline__ void mbar_wait(uint32_t bar, uint32_t parity) {
    uint32_t ok;
    int spins = 0;
    do {
        asm volatile("{\n.reg .pred p;\nmbarrier.try_wait.parity.shared::cta.b64 p, [%1], %2, %3;\nselp.u32 %0, 1, 0, p;\n}"
                     : "=r"(ok) : "r"(bar), "r"(parity), "r"(EGC_HINT) : "memory");
    } while (!ok && ++spins < (1 << 16));
}
__device__ __forceinline__ void tma_2d(uint32_t dst, const CUtensorMap* map, int c0, int c1, uint32_t bar) {
    asm volatile("cp.async.bulk.tensor.2d.shared::cluster.global.mbarrier::complete_tx::bytes [%0], [%1, {%3, %4}], [%2];"
                 ::"r"(dst), "l"(map), "r"(bar), "r"(c0), "r"(c1) : "memory");
}
__device__ __forceinline__ void tma_3d(uint32_t dst, const CUtensorMap* map, int c0, int c1, int c2, uint32_t bar) {
    asm volatile("cp.async.bulk.tensor.3d.shared::cluster.global.mbarrier::complete_tx::bytes [%0], [%1, {%3, %4, %5}], [%2];"
                 ::"r"(dst), "l"(map), "r"(bar), "r"(c0), "r"(c1), "r"(c2) : "memory");
}
__device__ __forceinline__ void cp_async16(uint32_t dst, const void* src) {
    asm volatile("cp.async.cg.shared.global [%0], [%1], 16;" ::"r"(dst), "l"(src) : "memory");
}
__device__ __forceinline__ void cp_async16_if(bool p, uint32_t dst, const void* src) {
    asm volatile("{\n.reg .pred p;\nsetp.ne.u32 p, %2, 0;\n@p cp.async.cg.shared.global [%0], [%1], 16;\n}" ::"r"(dst), "l"(src), "r"((uint32_t)p) : "memory");
}
__device__ __forceinline__ void sts32_if(bool p, uint32_t a, uint32_t v) {
    asm volatile("{\n.reg .pred p;\nsetp.ne.u32 p, %2, 0;\n@p st.shared.u32 [%0], %1;\n}" ::"r"(a), "r"(v), "r"((uint32_t)p) : "memory");
}
__device__ __forceinline__ void sts16_if(bool p, uint32_t a, uint32_t v) {
    asm volatile("{\n.reg .pred p;\nsetp.ne.u32 p, %2, 0;\n@p st.shared.u16 [%0], %1;\n}" ::"r"(a), "h"((uint16_t)v), "r"((uint32_t)p) : "memory");
}
__device__ __forceinline__ void sts8_if(bool p, uint32_t a, uint32_t v) {
    asm volatile("{\n.reg .pred p;\nsetp.ne.u32 p, %2, 0;\n@p st.shared.u8 [%0], %1;\n}" ::"r"(a), "r"(v), "r"((uint32_t)p) : "memory");
}
__device__ __forceinline__ void cp_async_wait_all() { asm volatile("cp.async.wait_all;" ::: "memory"); }

__device__ __forceinline__ uint32_t lds32(uint32_t a) { uint32_t v; asm volatile("ld.shared.u32 %0, [%1];" : "=r"(v) : "r"(a)); return v; }
__device__ __forceinline__ uint2 lds64(uint32_t a) { uint2 v; asm volatile("ld.shared.v2.u32 {%0,%1}, [%2];" : "=r"(v.x), "=r"(v.y) : "r"(a)); return v; }
__device__ __forceinline__ uint4 lds128(uint32_t a) {
    uint4 v; asm volatile("ld.shared.v4.u32 {%0,%1,%2,%3}, [%4];" : "=r"(v.x), "=r"(v.y), "=r"(v.z), "=r"(v.w) : "r"(a)); return v;
}
__device__ __forceinline__ void sts16(uint32_t a, uint32_t v) { asm volatile("st.shared.u16 [%0], %1;" ::"r"(a), "h"((uint16_t)v) : "memory"); }
__device__ __forceinline__ void sts32(uint32_t a, uint32_t v) { asm volatile("st.shared.u32 [%0], %1;" ::"r"(a), "r"(v) : "memory"); }
__device__ __forceinline__ void sts128(uint32_t a, uint4 v) {
    asm volatile("st.shared.v4.u32 [%0], {%1,%2,%3,%4};" ::"r"(a), "r"(v.x), "r"(v.y), "r"(v.z), "r"(v.w) : "memory");
}
__device__ __forceinline__ uint32_t pack_bf16(float lo, float hi) {
    uint32_t d; asm("cvt.rn.bf16x2.f32 %0, %1, %2;" : "=r"(d) : "f"(hi), "f"(lo)); return d;
}
__device__ __forceinline__ uint32_t seteq_bf16x2(uint32_t a, uint32_t b) {
    uint32_t d; asm("set.eq.bf16x2.bf16x2 %0, %1, %2;" : "=r"(d) : "r"(a), "r"(b)); return d;
}
__device__ __forceinline__ float tanh_approx(float x) { float y; asm("tanh.approx.f32 %0, %1;" : "=f"(y) : "f"(x)); return y; }
__device__ __forceinline__ uint32_t bf16_bits_of_int(int v) { return __float_as_uint((float)v) >> 16; }

__device__ __forceinline__ void mma_bf16(float (&d)[4], uint32_t a0, uint32_t a1, uint32_t a2, uint32_t a3,
                                         uint32_t b0, uint32_t b1, float c0, float c1, float c2, float c3) {
    asm("mma.sync.aligned.m16n8k16.row.col.f32.bf16.bf16.f32 {%0,%1,%2,%3}, {%4,%5,%6,%7}, {%8,%9}, {%10,%11,%12,%13};"
        : "=f"(d[0]), "=f"(d[1]), "=f"(d[2]), "=f"(d[3])
        : "r"(a0), "r"(a1), "r"(a2), "r"(a3), "r"(b0), "r"(b1), "f"(c0), "f"(c1), "f"(c2), "f"(c3));
}

__device__ __forceinline__ void mma_bf16_k8(float (&d)[4], uint32_t a0, uint32_t a1, uint32_t b0) {
    asm("mma.sync.aligned.m16n8k8.row.col.f32.bf16.bf16.f32 {%0,%1,%2,%3}, {%4,%5}, {%6}, {%0,%1,%2,%3};"
        : "+f"(d[0]), "+f"(d[1]), "+f"(d[2]), "+f"(d[3]) : "r"(a0), "r"(a1), "r"(b0));
}

__device__ __forceinline__ void wgmma_n80(float (&d)[40], uint64_t da, uint64_t db, int scale_d) {
    asm volatile(
        "{\n.reg .pred p;\nsetp.ne.b32 p, %42, 0;\n"
        "wgmma.mma_async.sync.aligned.m64n80k16.f32.bf16.bf16 "
        "{%0,%1,%2,%3,%4,%5,%6,%7,%8,%9,%10,%11,%12,%13,%14,%15,%16,%17,%18,%19,"
        "%20,%21,%22,%23,%24,%25,%26,%27,%28,%29,%30,%31,%32,%33,%34,%35,%36,%37,%38,%39}, "
        "%40, %41, p, 1, 1, 1, 0;\n}"
        : "+f"(d[0]), "+f"(d[1]), "+f"(d[2]), "+f"(d[3]), "+f"(d[4]), "+f"(d[5]), "+f"(d[6]), "+f"(d[7]),
          "+f"(d[8]), "+f"(d[9]), "+f"(d[10]), "+f"(d[11]), "+f"(d[12]), "+f"(d[13]), "+f"(d[14]), "+f"(d[15]),
          "+f"(d[16]), "+f"(d[17]), "+f"(d[18]), "+f"(d[19]), "+f"(d[20]), "+f"(d[21]), "+f"(d[22]), "+f"(d[23]),
          "+f"(d[24]), "+f"(d[25]), "+f"(d[26]), "+f"(d[27]), "+f"(d[28]), "+f"(d[29]), "+f"(d[30]), "+f"(d[31]),
          "+f"(d[32]), "+f"(d[33]), "+f"(d[34]), "+f"(d[35]), "+f"(d[36]), "+f"(d[37]), "+f"(d[38]), "+f"(d[39])
        : "l"(da), "l"(db), "r"(scale_d));
}
__device__ __forceinline__ void wgmma_fence() { asm volatile("wgmma.fence.sync.aligned;" ::: "memory"); }
__device__ __forceinline__ void wgmma_commit() { asm volatile("wgmma.commit_group.sync.aligned;" ::: "memory"); }
template <int N> __device__ __forceinline__ void wgmma_wait() { asm volatile("wgmma.wait_group.sync.aligned %0;" ::"n"(N) : "memory"); }

__device__ __forceinline__ uint64_t smem_desc(uint32_t addr) {
    return (uint64_t)((addr & 0x3FFFF) >> 4) | ((uint64_t)1 << 16) | ((uint64_t)64 << 32) | ((uint64_t)1 << 62);
}

__device__ __forceinline__ unsigned int grid_target(const unsigned int* ctr) {
    unsigned int v;
    asm volatile("ld.relaxed.gpu.global.u32 %0, [%1];" : "=r"(v) : "l"(ctr) : "memory");
    return (v / NT + 1u) * NT;
}
__device__ __forceinline__ void grid_arrive(unsigned int* ctr) {
    asm volatile("red.release.gpu.global.add.u32 [%0], 1;" ::"l"(ctr) : "memory");
}
__device__ __forceinline__ void grid_arrive_relaxed(unsigned int* ctr) {
    asm volatile("red.relaxed.gpu.global.add.u32 [%0], 1;" ::"l"(ctr) : "memory");
}
__device__ __forceinline__ void grid_wait(const unsigned int* ctr, unsigned int target) {
    unsigned int v;
    int spins = 0;
    do {
        asm volatile("ld.acquire.gpu.global.u32 %0, [%1];" : "=r"(v) : "l"(ctr) : "memory");
    } while ((int)(v - target) < 0 && ++spins < (1 << 21));
}

constexpr int GCNT = MISC_OFF + 64;

__device__ __forceinline__ uint32_t bin_rank(uint32_t sb, uint32_t w) {
    uint32_t rank;
    asm volatile("{\n.reg .pred p;\nsetp.lt.u32 p, %1, %3;\nmov.u32 %0, 0xFFFF;\n@p atom.shared.add.u32 %0, [%2], 1;\n}"
                 : "=r"(rank) : "r"(w >> 24), "r"(sb + GCNT + ((w >> 25) & 0x3C)), "n"(TILE) : "memory");
    return rank;
}
__device__ __forceinline__ void bin_store(uint32_t sb, uint32_t w, uint32_t rank, uint32_t row) {
    const uint32_t idx = (w >> 27) * CAPG + rank;
    sts32_if(rank < CAPG, sb + EL_OFF + idx * 4, w);
    sts8_if(rank < CAPG, sb + ER_OFF + idx, row);
}
__device__ __forceinline__ bool bar_or(int id, int n, bool v) {
    uint32_t r;
    asm volatile("{\n.reg .pred p, q;\nsetp.ne.u32 q, %3, 0;\nbarrier.cta.red.or.pred p, %1, %2, q;\nselp.u32 %0, 1, 0, p;\n}"
                 : "=r"(r) : "r"(id), "r"(n), "r"((uint32_t)v) : "memory");
    return r;
}

__device__ __forceinline__ int layout_list(uint32_t sb, int t, int last) {
    int tot[10];
    {
        const uint4 a = lds128(sb + GCNT), b = lds128(sb + GCNT + 16);
        const uint2 c = lds64(sb + GCNT + 32);
        tot[0] = a.x; tot[1] = a.y; tot[2] = a.z; tot[3] = a.w; tot[4] = b.x; tot[5] = b.y; tot[6] = b.z; tot[7] = b.w;
        tot[8] = c.x; tot[9] = c.y;
    }
    int run = 0, myend = 0, gap = 0, tab = 0, mx = 0;
#pragma unroll
    for (int g = 0; g < 10; g++) {
        const int ge = run + ((tot[g] + 15) & ~15);
        const int off = t * 16 - run;
        if (off >= 0 && t * 16 < ge) tab = ((g * CAPG + off) << 16) | (tot[g] - off);
        if (g == t) myend = ge;
        if (g == 4) gap = ge;
        mx = max(mx, tot[g]);
        run = ge + (g == 4 ? 32 : 0);
    }
    if (mx > CAPG || run > CAP_STEPS * 16) return -1;
    if (t < CAP_STEPS) sts32(sb + CNT_OFF + t * 4, tab);
    if (t < 32) sts32(sb + MR_OFF + ((run >> 4) + (t >> 4)) * 128 + ((t & 15) >> 1) * 16 + (t & 1) * 4, 0xFFFFFFFFu);
    if (t < 10) sts32(sb + MISC_OFF + t * 4, myend >> 4);
    if (t == 10) sts32(sb + MISC_OFF + 40, (gap >> 4) + 2);
    if (t == 11) sts32(sb + MISC_OFF + 44, last);
    return run;
}

__device__ __forceinline__ void expand_meta(uint32_t sb, int t, int run) {
#pragma unroll 2
    for (int pos = t; pos < run; pos += N_AUX) {
        const uint32_t tb = lds32(sb + CNT_OFF + (pos >> 4) * 4);
        const int k = pos & 15, st16 = pos & ~15;
        const bool v = k < (int)(tb & 0xFFFF);
        const uint32_t idx = v ? (tb >> 16) + k : 0;
        const uint32_t w = lds32(sb + EL_OFF + idx * 4);
        uint32_t row;
        asm volatile("ld.shared.u8 %0, [%1];" : "=r"(row) : "r"(sb + ER_OFF + idx));
        const uint32_t se = w & 0xFFFFFF, sn = se / EPC;
        const uint32_t dbf = v ? bf16_bits_of_int((w >> 24) & 7) : DBF_INV;
        const uint32_t mr = sb + MR_OFF + st16 * 8 + (k & 7) * 16 + (k >> 3) * 4;
        sts32(mr, v ? sn : 0xFFFFFFFFu);
        sts32(mr + 8, dbf * 0x10001u);
        sts16(sb + MQ_OFF + (st16 + ((k & 7) >> 1) * 4 + (k & 1) + 2 * (k >> 3)) * 2, dbf);
        sts32(sb + CAND_OFF + pos * 4, v ? ((row - sn) * EPC + se) * 32 : 0xFFFFFFFFu);
    }
}

__device__ __forceinline__ void gather_attr(uint32_t sb, int t, int run, const __nv_bfloat16* __restrict__ e_attr) {
    const int h = t & 1, p0 = t >> 1;
    const char* base = (const char*)e_attr + h * 16;
    uint32_t src = sb + CAND_OFF + p0 * 4;
    uint32_t dst = sb + EATTR_OFF + p0 * 32 + ((h ^ ((p0 >> 2) & 1)) << 4);
#pragma unroll 1
    for (int pos = p0; pos < run; pos += 4 * 64) {
        uint32_t off[4];
#pragma unroll
        for (int i = 0; i < 4; i++) off[i] = lds32(src + i * 256);
#pragma unroll
        for (int i = 0; i < 4; i++) {
            if (pos + i * 64 < run)
                asm volatile("{\n.reg .pred p;\n.reg .b32 n, o;\n.reg .b64 a;\nsetp.ne.u32 p, %1, 0xFFFFFFFF;\nselp.b32 n, 16, 0, p;\n"
                             "selp.b32 o, %1, 0, p;\ncvt.u64.u32 a, o;\nadd.u64 a, a, %2;\ncp.async.cg.shared.global [%0], [a], 16, n;\n}"
                             ::"r"(dst + i * 2048), "r"(off[i]), "l"(base) : "memory");
        }
        src += 1024;
        dst += 8192;
    }
    if (t == 0) PROF2(113);
    cp_async_wait_all();
    if (t == 0) PROF2(114);
}

struct Params {
    const __nv_bfloat16* e_attr;
    const int* src;
    const int* dst;
    const __nv_bfloat16* g_w;
    const __nv_bfloat16* v_w;
    const __nv_bfloat16* u_w;
    __nv_bfloat16* out;
    uint4* tab;
    uint4* slots;
    unsigned int* bar;
};

__global__ void __launch_bounds__(NTHREADS, 1)
egc_kernel(const __grid_constant__ CUtensorMap tm_x, const __grid_constant__ CUtensorMap tm_g,
           const __grid_constant__ CUtensorMap tm_v, const __grid_constant__ CUtensorMap tm_u,
           const __grid_constant__ CUtensorMap tm_t, const __grid_constant__ CUtensorMap tm_c,
           const __grid_constant__ CUtensorMap tm_s,
           const __grid_constant__ Params P) {
    extern __shared__ __align__(1024) unsigned char smem_raw[];
    const uint32_t sb = (uint32_t)__cvta_generic_to_shared(smem_raw);
    if (sb & 1023u) __trap();
    const int tid = threadIdx.x, warp = tid >> 5, lane = tid & 31;
    const int tile = blockIdx.x;
    const uint32_t bar_full = sb + BAR_OFF, bar_empty = bar_full + 8 * NST, bar_x = bar_empty + 8 * NST, bar_idx = bar_x + 32, bar_c = bar_idx + 8, bar_meta = bar_c + 8;
    const __nv_bfloat16* __restrict__ e_attr = P.e_attr;

    int4 dv, sv;
    if (warp < 16) {
        if (tid < EPC / 4) {
            asm volatile("ld.global.nc.v4.s32 {%0,%1,%2,%3}, [%4];" : "=r"(dv.x), "=r"(dv.y), "=r"(dv.z), "=r"(dv.w)
                         : "l"((const int4*)P.dst + tile * (EPC / 4) + tid));
            asm volatile("ld.global.nc.v4.s32 {%0,%1,%2,%3}, [%4];" : "=r"(sv.x), "=r"(sv.y), "=r"(sv.z), "=r"(sv.w)
                         : "l"((const int4*)P.src + tile * (EPC / 4) + tid));
        }
        sts128(sb + CAND_OFF + tid * 16, make_uint4(REC_INV, REC_INV, REC_INV, REC_INV));
        sts128(sb + CAND_OFF + (tid + 512) * 16, make_uint4(REC_INV, REC_INV, REC_INV, REC_INV));
        if (tid < 128) sts32(sb + CNT_OFF + tid * 4, 0);
        if (tid == 0) { PROF(0); PROF2(64); }
    } else if (warp < 20) {
        if (tid < N_MAIN + 16) sts32(sb + GCNT + (tid - N_MAIN) * 4, 0);
    } else if (tid == 640) {
        asm volatile("prefetch.tensormap [%0];" ::"l"(&tm_g) : "memory");
#pragma unroll
        for (int s = 0; s < NST; s++) {
            mbar_init(bar_full + 8 * s, 1);
            mbar_init(bar_empty + 8 * s, 16);
        }
        asm volatile("fence.mbarrier_init.release.cluster;" ::: "memory");
#pragma unroll 1
        for (int it = 0; it < NST; it++) {
            mbar_expect_tx(bar_full + 8 * it, 32768);
            tma_3d(sb + RING_OFF + it * 32768, &tm_g, 0, 256 + it * 64, 0, bar_full + 8 * it);
        }
    } else if (tid == 704) {
        asm volatile("prefetch.tensormap [%0];" ::"l"(&tm_x) : "memory");
#pragma unroll
        for (int s = 0; s < 4; s++) mbar_init(bar_x + 8 * s, 1);
        mbar_init(bar_idx, EPC / 128);
        mbar_init(bar_c, 1);
        mbar_init(bar_meta, 4);
        asm volatile("fence.mbarrier_init.release.cluster;" ::: "memory");
#pragma unroll 1
        for (int c = 0; c < X_EARLY; c++) {
            mbar_expect_tx(bar_x + 8 * c, 10240);
            tma_2d(sb + X_OFF + c * 10240, &tm_x, c * 64, tile * TILE, bar_x + 8 * c);
        }
    } else if (tid == 672) {
        asm volatile("prefetch.tensormap [%0];" ::"l"(&tm_v) : "memory");
        asm volatile("prefetch.tensormap [%0];" ::"l"(&tm_u) : "memory");
        asm volatile("prefetch.tensormap [%0];" ::"l"(&tm_t) : "memory");
        asm volatile("prefetch.tensormap [%0];" ::"l"(&tm_c) : "memory");
        asm volatile("prefetch.tensormap [%0];" ::"l"(&tm_s) : "memory");
        const int go = tile * 2176, vo = tile * 1056;
        const int gn = min(2176, 528 * 512 - go), vn = min(1056, 256 * 512 - vo);
        if (gn > 0) asm volatile("cp.async.bulk.prefetch.L2.global [%0], %1;" ::"l"((const char*)P.g_w + go), "r"(gn) : "memory");
        if (vn > 0) {
            asm volatile("cp.async.bulk.prefetch.L2.global [%0], %1;" ::"l"((const char*)P.v_w + vo), "r"(vn) : "memory");
            asm volatile("cp.async.bulk.prefetch.L2.global [%0], %1;" ::"l"((const char*)P.u_w + vo), "r"(vn) : "memory");
        }
    }
    __syncthreads();

    if (warp >= 20) {
        asm volatile("setmaxnreg.dec.sync.aligned.u32 24;");
        if (tid == 640) {
            int st = 0, par = 0;
#pragma unroll 1
            for (int it = NST; it < NIT; it++) {
                const int p = it >> 2;
                const CUtensorMap* m = (p == 1) ? &tm_v : (p == 3) ? &tm_u : &tm_g;
                const int row = ((p == 0) ? 256 : 0) + (it & 3) * 64;
                mbar_wait(bar_empty + 8 * st, par);
                mbar_expect_tx(bar_full + 8 * st, 32768);
                tma_3d(sb + RING_OFF + st * 32768, m, 0, row, 0, bar_full + 8 * st);
                if (++st == NST) { st = 0; par ^= 1; }
            }
            mbar_wait(bar_empty + 8 * 1, 0);
            mbar_expect_tx(bar_c, 8192);
            tma_3d(sb + CT_OFF, &tm_c, 0, 512, 0, bar_c);
        } else if (tid == 704) {
            if (X_EARLY < 4) mbar_wait(bar_idx, 0);
#pragma unroll 1
            for (int c = X_EARLY; c < 4; c++) {
                mbar_expect_tx(bar_x + 8 * c, 10240);
                tma_2d(sb + X_OFF + c * 10240, &tm_x, c * 64, tile * TILE, bar_x + 8 * c);
            }
        } else if (warp == 21) {
            mbar_wait(bar_x + 8 * 3, 0);
#pragma unroll 1
            for (int i = lane; i < EPC * 32 / 128; i += 32)
                asm volatile("prefetch.global.L2 [%0];" ::"l"((const char*)e_attr + (size_t)tile * EPC * 32 + i * 128) : "memory");
        } else if (warp == 23) {
            unsigned int target = 0;
            if (lane == 0) target = grid_target(P.bar);
#pragma unroll 1
            for (int wave = 0; wave < 2; wave++) {
                bar_sync(BAR_TABLE, N_MAIN + 32);
                if (lane == 0) {
#pragma unroll 1
                    for (int ds = 0; ds < 8; ds++) {
                        asm volatile("cp.async.bulk.tensor.2d.global.shared::cta.bulk_group [%0, {%2, %3}], [%1];"
                                     ::"l"(&tm_t), "r"(sb + EATTR_OFF + ds * 5120), "r"(ds * 64), "r"(tile * TILE + wave * 40) : "memory");
                        asm volatile("cp.async.bulk.commit_group;" ::: "memory");
                        asm volatile("cp.async.bulk.wait_group.read %0;" ::"n"(EGC_STQ) : "memory");
                    }
                    asm volatile("cp.async.bulk.wait_group.read 0;" ::: "memory");
                }
                __syncwarp();
                if (wave == 0) bar_arrive(BAR_STG, N_MAIN + 32);
                else bar_arrive(BAR_XFREE, N_AUX + 32);
            }
            if (lane == 0) {
                asm volatile("cp.async.bulk.wait_group 0;" ::: "memory");
                PROF(6);
                grid_arrive_relaxed(P.bar);
                grid_wait(P.bar, target);
                PROF(4);
            }
            __syncwarp();
            bar_arrive(BAR_GO, N_MAIN + 32);
        }
    } else if (warp >= 16) {
        asm volatile("setmaxnreg.dec.sync.aligned.u32 40;");
        const int t = tid - N_MAIN;
        unsigned int target = 0;
        if (t == 0) target = grid_target(P.bar + 32);
        bar_sync(BAR_S1, N_MAIN + N_AUX);
        if (t == 0) {
            PROF(1);
            asm volatile("cp.async.bulk.tensor.3d.global.shared::cta.bulk_group [%0, {%2, %3, %2}], [%1];"
                         ::"l"(&tm_s), "r"(sb + CAND_OFF), "r"(0), "r"(tile) : "memory");
            asm volatile("cp.async.bulk.commit_group;" ::: "memory");
            asm volatile("cp.async.bulk.wait_group 0;" ::: "memory");
            PROF(13);
            grid_arrive_relaxed(P.bar + 32);
            grid_wait(P.bar + 32, target);
            PROF(2); PROF2(99);
        }
        bar_sync(BAR_AUX, N_AUX);
        const uint32_t row = sb + CAND_OFF + t * 32;
#pragma unroll 1
        for (int j = 0; j < 8; j++) {
            const uint32_t a = row + (j >> 1) * 4096 + (j & 1) * 16;
            if (t < NT) cp_async16(a, P.slots + (size_t)(tile * NT + t) * 8 + j);
            else sts128(a, make_uint4(REC_INV, REC_INV, REC_INV, REC_INV));
        }
        cp_async_wait_all();
        if (t == 0) PROF2(100);
        bool ovf = false;
#pragma unroll 1
        for (int j = 0; j < 4; j++) {
            const uint4 a = lds128(row + j * 4096), b = lds128(row + j * 4096 + 16);
            if (j >= 2 && !__any_sync(0xffffffffu, rec_dl(a.x) != 127)) break;
            const uint32_t rec[8] = {a.x, a.y, a.z, a.w, b.x, b.y, b.z, b.w};
            uint32_t rank[8];
#pragma unroll
            for (int i = 0; i < 8; i++) rank[i] = bin_rank(sb, rec[i]);
#pragma unroll
            for (int i = 0; i < 8; i++) bin_store(sb, rec[i], rank[i], t);
            ovf |= rec_dl(b.w) == 126;
        }
        if (t == 0) PROF2(101);
        ovf = bar_or(BAR_AUX, N_AUX, ovf);
        if (t == 0) { PROF(11); PROF2(105); }
        int run = ovf ? -1 : layout_list(sb, t, 1);
        if (run >= 0) {
            bar_sync(BAR_AUX, N_AUX);
            if (t == 0) PROF2(107);
            expand_meta(sb, t, run);
            if (t == 0) PROF2(108);
            __syncwarp();
            if ((t & 31) == 0) mbar_arrive(bar_meta);
            bar_sync(BAR_AUX, N_AUX);
            bar_sync(BAR_XFREE, N_AUX + 32);
            if (t == 0) PROF2(111);
            gather_attr(sb, t, run, e_attr);
            if (t == 0) PROF(3);
            bar_arrive(BAR_READY, N_MAIN + N_AUX);
        } else {
            bar_sync(BAR_AUX, N_AUX);
            if (t < 16) sts32(sb + GCNT + t * 4, 0);
            bar_sync(BAR_AUX, N_AUX);
            bool first = true;
#pragma unroll 1
            for (int w0 = 0; w0 < NT * EPC; w0 += 128) {
                const int e = w0 + t, d = __ldg(P.dst + e), b = (unsigned)d / TILE;
                uint32_t w = REC_INV;
                const int c = (unsigned)e / EPC;
                if (b == tile) w = ((uint32_t)(d - b * TILE) << 24) | (__ldg(P.src + e) * EPC + (e - c * EPC));
                bin_store(sb, w, bin_rank(sb, w), c);
                bar_sync(BAR_AUX, N_AUX);
                int mx = 0, sum = 0;
#pragma unroll 1
                for (int g = 0; g < 10; g++) { const int v = lds32(sb + GCNT + g * 4); mx = max(mx, v); sum += v; }
                const bool fin = w0 + 128 >= NT * EPC;
                const bool flush = fin || mx > CAPG - 128 || sum > CAP_STEPS * 16 - 32 - 150 - 128;
                bar_sync(BAR_AUX, N_AUX);
                if (flush) {
                    if (first) bar_sync(BAR_XFREE, N_AUX + 32);
                    first = false;
                    run = layout_list(sb, t, fin);
                    bar_sync(BAR_AUX, N_AUX);
                    expand_meta(sb, t, run);
                    bar_sync(BAR_AUX, N_AUX);
                    gather_attr(sb, t, run, e_attr);
                    bar_arrive(BAR_READY, N_MAIN + N_AUX);
                    if (!fin) bar_sync(BAR_CONSUMED, N_MAIN + N_AUX);
                    bar_sync(BAR_AUX, N_AUX);
                    if (t < 16) sts32(sb + GCNT + t * 4, 0);
                    bar_sync(BAR_AUX, N_AUX);
                }
            }
        }
    } else {
        asm volatile("setmaxnreg.inc.sync.aligned.u32 104;");
        const int wg = warp >> 2;
        const int r = lane >> 2, q = lane & 3;
        if (tid < EPC / 4) {
            const int dd[4] = {dv.x, dv.y, dv.z, dv.w};
            const int ss[4] = {sv.x, sv.y, sv.z, sv.w};
            uint32_t rank[4];
            int bb[4];
#pragma unroll
            for (int i = 0; i < 4; i++) {
                bb[i] = (unsigned)dd[i] / TILE;
                asm volatile("atom.shared.add.u32 %0, [%1], 1;" : "=r"(rank[i]) : "r"(sb + CNT_OFF + bb[i] * 4) : "memory");
            }
#pragma unroll
            for (int i = 0; i < 4; i++) {
                const uint32_t rec = ((uint32_t)(dd[i] - bb[i] * TILE) << 24) | (ss[i] * EPC + tid * 4 + i);
                sts32(sb + CAND_OFF + bb[i] * 128 + (min(rank[i], 31u) << 2), rank[i] < 31 ? rec : REC_OVF);
            }
            __syncwarp();
            if (lane == 0) mbar_arrive(bar_idx);
        }
        if (tid == 0) PROF(14);
        asm volatile("fence.proxy.async.shared::cta;" ::: "memory");
        bar_arrive(BAR_S1, N_MAIN + N_AUX);

        float d[40];
        uint32_t pB[20], pV[20], xa[20];
        const uint64_t da0 = smem_desc(sb + RING_OFF + wg * 8192), db0 = smem_desc(sb + X_OFF);
        const bool odd = r & 1;

        auto stage = [&](const int it) {
            const int c = it & 3, st = it % NST;
            if (it < 4) mbar_wait(bar_x + 8 * c, 0);
            if (it == 0 && tid == 0) PROF(5);
            mbar_wait(bar_full + 8 * st, (it / NST) & 1);
            if (tid == 0) PROF2(it);
            wgmma_fence();
            const uint64_t da = da0 + st * 2048, db = db0 + c * 640;
            wgmma_n80(d, da, db, c != 0);
            wgmma_n80(d, da + 128, db + 2, 1);
            wgmma_n80(d, da + 256, db + 4, 1);
            wgmma_n80(d, da + 384, db + 6, 1);
            wgmma_commit();
        };
        auto release = [&](const int it) {
            if ((it + NST < NIT || it == 13) && lane == 0) mbar_arrive(bar_empty + 8 * (it % NST));
        };

        auto stage_table = [&](const int wave) {
            const uint32_t base = sb + EATTR_OFF + (warp >> 1) * 5120 + (r & 1) * 8 + 2 * q * 128;
            const uint32_t ch = (warp & 1) * 4 + (r >> 1);
#pragma unroll
            for (int jj = 0; jj < 10; jj++) {
                const int j = wave * 10 + jj;
                const uint32_t rv = __shfl_xor_sync(0xffffffffu, odd ? pB[j] : pV[j], 4);
                asm volatile("st.shared.v2.u32 [%0], {%1, %2};"
                             ::"r"(base + ((jj >> 1) * 8 + (jj & 1)) * 128 + ((ch ^ (2 * q + (jj & 1))) << 4)),
                               "r"(odd ? rv : pB[j]), "r"(odd ? pV[j] : rv) : "memory");
            }
            asm volatile("fence.proxy.async.shared::cta;" ::: "memory");
            bar_arrive(BAR_TABLE, N_MAIN + 32);
        };
#pragma unroll
        for (int p = 0; p < 4; p++) {
#pragma unroll
            for (int c = 0; c < 4; c++) {
                stage(p * 4 + c);
                if (p == 2 && c == 0) {
                    stage_table(0);
                }
                if (p * 4 + c == EGC_WAVE2) { bar_sync(BAR_STG, N_MAIN + 32); stage_table(1); }
                if (c > 0) { wgmma_wait<1>(); release(p * 4 + c - 1); }
            }
            wgmma_wait<0>();
            release(p * 4 + 3);
            if (p == 0) {
#pragma unroll
                for (int j = 0; j < 10; j++) {
                    pB[2 * j] = pack_bf16(0.5f * d[4 * j], 0.5f * d[4 * j + 2]);
                    pB[2 * j + 1] = pack_bf16(0.5f * d[4 * j + 1], 0.5f * d[4 * j + 3]);
                }
            } else if (p == 1) {
#pragma unroll
                for (int j = 0; j < 10; j++) {
                    pV[2 * j] = pack_bf16(0.5f * d[4 * j], 0.5f * d[4 * j + 2]);
                    pV[2 * j + 1] = pack_bf16(0.5f * d[4 * j + 1], 0.5f * d[4 * j + 3]);
                }
            } else if (p == 2) {
#pragma unroll
                for (int j = 0; j < 20; j++) xa[j] = pack_bf16(0.5f * d[2 * j], 0.5f * d[2 * j + 1]);
            }
        }
        if (tid == 0) { PROF(7); PROF2(109); }

        uint32_t cf[2][4];
            mbar_wait(bar_c, 0);
#pragma unroll
            for (int c = 0; c < 2; c++) {
                const int k = (lane >> 4) * 8 + (lane & 7), col = (warp & 7) * 32 + c * 16 + ((lane >> 3) & 1) * 8;
                asm volatile("ldmatrix.sync.aligned.m8n8.x4.trans.shared.b16 {%0,%1,%2,%3}, [%4];"
                             : "=r"(cf[c][0]), "=r"(cf[c][1]), "=r"(cf[c][2]), "=r"(cf[c][3])
                             : "r"(sb + CT_OFF + (col >> 6) * 2048 + k * 128 + ((((col & 63) >> 3) ^ (k & 7)) << 4)));
#pragma unroll
                for (int i = 0; i < 4; i++)
                    asm("mul.rn.bf16x2 %0, %0, %1;" : "+r"(cf[c][i]) : "r"(0x3F003F00u));
            }
        bar_sync(BAR_MAIN, N_MAIN);
#pragma unroll
        for (int j = 0; j < 10; j++) {
            sts128(sb + PARK_ACC + (warp * 10 + j) * 512 + lane * 16,
                   make_uint4(__float_as_uint(d[4 * j]), __float_as_uint(d[4 * j + 1]), __float_as_uint(d[4 * j + 2]), __float_as_uint(d[4 * j + 3])));
            asm volatile("st.shared.v2.u32 [%0], {%1, %2};" ::"r"(sb + PARK_XA + (warp * 10 + j) * 256 + lane * 8), "r"(xa[2 * j]), "r"(xa[2 * j + 1]) : "memory");
        }
        bar_sync(BAR_MAIN, N_MAIN);

        {
            const int ds = warp & 7, set = warp >> 3;
            const uint32_t cA = bf16_bits_of_int(2 * q) | (bf16_bits_of_int(2 * q + 1) << 16);
            const uint32_t cB = bf16_bits_of_int(r) * 0x10001u;
            const uint32_t ia0 = (r == 2 * q) ? 0x00003F80u : 0u, ia1 = ia0 << 16;
            const uint32_t ia2 = (r == 2 * q + 1) ? 0x00003F80u : 0u, ia3 = ia2 << 16;
            const char* tabl = (const char*)P.tab + ds * 128 + q * 16;
            const int ek = (lane >> 4) * 8 + (lane & 7);
            const uint32_t ea_l = sb + EATTR_OFF + ek * 32 + ((((lane >> 3) & 1) ^ ((ek >> 2) & 1)) << 4);
            const uint32_t mr_l = sb + MR_OFF + r * 16;
            const uint32_t mq_l = sb + MQ_OFF + q * 8;
            const uint32_t bounce = sb + CAND_OFF + warp * 512;
            const uint32_t pk_acc = sb + PARK_ACC + (ds * 20 + set * 5) * 512 + lane * 16;
            const uint32_t pk_xa = sb + PARK_XA + (ds * 20 + set * 5) * 256 + lane * 8;

            uint4 bx[4], by[4];
#pragma unroll
            for (int i = 0; i < 4; i++) { bx[i] = make_uint4(0, 0, 0, 0); by[i] = make_uint4(0, 0, 0, 0); }
            const uint32_t ybuf = (warp < 8 ? sb + YB_OFF + warp * 2048
                                            : warp < 12 ? sb + CAND_OFF + 8192 + (warp - 8) * 2048 : sb + EL_OFF + (warp - 12) * 2048) + lane * 16;

            auto gather_reg = [&](uint4& b0, uint4& b1, uint32_t w) {
                asm volatile("{\n.reg .pred p;\n.reg .b64 a;\nsetp.ge.s32 p, %8, 0;\nmad.wide.u32 a, %8, 1024, %9;\n"
                             "@p ld.global.cg.v4.u32 {%0,%1,%2,%3}, [a];\n@p ld.global.cg.v4.u32 {%4,%5,%6,%7}, [a+64];\n}"
                             : "+r"(b0.x), "+r"(b0.y), "+r"(b0.z), "+r"(b0.w), "+r"(b1.x), "+r"(b1.y), "+r"(b1.z), "+r"(b1.w)
                             : "r"(w), "l"(tabl));
            };
            auto gather_smem = [&](uint32_t dst, uint32_t w) {
                asm volatile("{\n.reg .pred p;\n.reg .b64 a;\nsetp.ge.s32 p, %1, 0;\nmad.wide.u32 a, %1, 1024, %2;\n"
                             "@p cp.async.cg.shared.global [%0], [a], 16;\n@p cp.async.cg.shared.global [%0+512], [a+64], 16;\n}"
                             ::"r"(dst), "r"(w), "l"(tabl) : "memory");
            };

            if (tid == 0) PROF2(110);
            bar_sync(BAR_GO, N_MAIN + 32);
            if (tid == 0) PROF2(112);
            for (;;) {
                bar_sync(BAR_READY, N_MAIN + N_AUX);
                if (tid == 0) { asm volatile("" ::: "memory"); PROF(8); PROF2(66); }
                const int last = lds32(sb + MISC_OFF + 44);
                int i = set ? (int)lds32(sb + MISC_OFF + 40) : 0;
                uint32_t pe = ea_l + i * 512, pr = mr_l + i * 128, pq = mq_l + i * 32;
                {
#pragma unroll
                    for (int k = 0; k < 4; k++) sts128(ybuf + k * 512, make_uint4(0, 0, 0, 0));
                    const uint2 w0 = lds64(pr), w1 = lds64(pr + 128);
                    gather_reg(bx[0], bx[1], w0.x);
                    gather_reg(bx[2], bx[3], w0.y);
                    gather_smem(ybuf, w1.x);
                    gather_smem(ybuf + 1024, w1.y);
                }
                int ph = 0;
                for (int g = 0; g < 5; g++) {
                    const int gend = lds32(sb + MISC_OFF + (set * 5 + g) * 4);
                    float acc[2][4];
                    uint2 xf[2];
#pragma unroll
                    for (int c = 0; c < 2; c++) {
                        const uint4 a = lds128(pk_acc + (c * 10 + g) * 512);
                        acc[c][0] = __uint_as_float(a.x); acc[c][1] = __uint_as_float(a.y);
                        acc[c][2] = __uint_as_float(a.z); acc[c][3] = __uint_as_float(a.w);
                        xf[c] = lds64(pk_xa + (c * 10 + g) * 256);
                    }

                    auto step = [&](uint4 (&cur)[4], const int k) {
                        const uint2 wn = lds64(pr + (k + 2) * 128);
                        if (k == 1) {
                            cp_async_wait_all();
#pragma unroll
                            for (int i = 0; i < 4; i++) cur[i] = lds128(ybuf + i * 512);
                            gather_smem(ybuf, wn.x);
                            gather_smem(ybuf + 1024, wn.y);
                        }
                        const uint2 dd = lds64(pr + k * 128 + 8);
                        const uint2 db = lds64(pq + k * 32);
                        uint32_t e0, e1, e2, e3;
                        asm volatile("ldmatrix.sync.aligned.m8n8.x4.shared.b16 {%0,%1,%2,%3}, [%4];"
                                     : "=r"(e0), "=r"(e1), "=r"(e2), "=r"(e3) : "r"(pe + k * 512));
                        const uint32_t sa0 = seteq_bf16x2(dd.x, cA), sa1 = seteq_bf16x2(dd.y, cA);
                        const uint32_t sb0 = seteq_bf16x2(db.x, cB), sb1 = seteq_bf16x2(db.y, cB);
#pragma unroll
                        for (int c = 0; c < 2; c++) {
                            float p0[4], p1[4], h0[4], h1[4];
                            mma_bf16(p0, cf[c][0], cf[c][1], cf[c][2], cf[c][3], e0, e1, 0.f, 0.f, 0.f, 0.f);
                            mma_bf16(p1, cf[c][0], cf[c][1], cf[c][2], cf[c][3], e2, e3, 0.f, 0.f, 0.f, 0.f);
                            mma_bf16_k8(p0, xf[c].x, xf[c].y, sa0);
                            mma_bf16_k8(p1, xf[c].x, xf[c].y, sa1);
                            mma_bf16(p0, ia0, ia1, ia2, ia3, cur[c].x, cur[c].y, p0[0], p0[1], p0[2], p0[3]);
                            mma_bf16(p1, ia0, ia1, ia2, ia3, cur[2 + c].x, cur[2 + c].y, p1[0], p1[1], p1[2], p1[3]);
                            mma_bf16(h0, ia0, ia1, ia2, ia3, cur[c].z, cur[c].w, 0.f, 0.f, 0.f, 0.f);
                            mma_bf16(h1, ia0, ia1, ia2, ia3, cur[2 + c].z, cur[2 + c].w, 0.f, 0.f, 0.f, 0.f);
                            if (k == 0 && c == 1) {
                                gather_reg(cur[0], cur[1], wn.x);
                                gather_reg(cur[2], cur[3], wn.y);
                            }
                            float m0[4], m1[4];
#pragma unroll
                            for (int j = 0; j < 4; j++) {
                                m0[j] = fmaf(tanh_approx(p0[j]), h0[j], h0[j]);
                                m1[j] = fmaf(tanh_approx(p1[j]), h1[j], h1[j]);
                            }
                            mma_bf16(acc[c], pack_bf16(m0[0], m0[1]), pack_bf16(m0[2], m0[3]), pack_bf16(m1[0], m1[1]), pack_bf16(m1[2], m1[3]),
                                     sb0, sb1, acc[c][0], acc[c][1], acc[c][2], acc[c][3]);
                        }
                    };

                    int rem = gend - i;
                    i = gend;
                    while (rem > 0) {
                        if (ph == 0) {
                            step(bx, 0);
                            ph = 1;
                            if (--rem == 0) break;
                        }
                        step(by, 1);
                        ph = 0; pe += 2 * 512; pr += 2 * 128; pq += 2 * 32; --rem;
                    }

                    if (last) {
                        uint32_t o[4];
#pragma unroll
                        for (int c = 0; c < 2; c++) {
                            float z[4];
#pragma unroll
                            for (int j = 0; j < 4; j++) z[j] = __fdividef(acc[c][j], 1.f + __expf(-acc[c][j]));
                            o[2 * c] = pack_bf16(z[0], z[1]);
                            o[2 * c + 1] = pack_bf16(z[2], z[3]);
                        }
                        asm volatile("stmatrix.sync.aligned.m8n8.x4.trans.shared.b16 [%0], {%1,%2,%3,%4};"
                                     ::"r"(bounce + (lane & 7) * 64 + (((lane >> 3) ^ ((lane >> 1) & 3)) << 4)),
                                       "r"(o[0]), "r"(o[1]), "r"(o[2]), "r"(o[3]) : "memory");
                        __syncwarp();
                        const int node = lane >> 2;
                        const uint4 v = lds128(bounce + node * 64 + ((q ^ ((node >> 1) & 3)) << 4));
                        *(uint4*)(P.out + (size_t)(tile * TILE + (set * 5 + g) * 8 + node) * DD + ds * 32 + q * 8) = v;
                        __syncwarp();
                    } else {
#pragma unroll
                        for (int c = 0; c < 2; c++)
                            sts128(pk_acc + (c * 10 + g) * 512, make_uint4(__float_as_uint(acc[c][0]), __float_as_uint(acc[c][1]),
                                                                           __float_as_uint(acc[c][2]), __float_as_uint(acc[c][3])));
                    }
                }
                if (last) break;
                cp_async_wait_all();
                bar_arrive(BAR_CONSUMED, N_MAIN + N_AUX);
            }
            if (tid == 0) { PROF(9); PROF2(65); }
        }
    }
}

typedef CUresult (*EncodeFn)(CUtensorMap*, CUtensorMapDataType, cuuint32_t, void*, const cuuint64_t*, const cuuint64_t*,
                             const cuuint32_t*, const cuuint32_t*, CUtensorMapInterleave, CUtensorMapSwizzle,
                             CUtensorMapL2promotion, CUtensorMapFloatOOBfill);

static void make_map(EncodeFn fn, CUtensorMap* m, const void* ptr, int rows, int box_rows) {
    cuuint64_t dims[2] = {(cuuint64_t)DD, (cuuint64_t)rows};
    cuuint64_t strides[1] = {(cuuint64_t)DD * 2};
    cuuint32_t box[2] = {64, (cuuint32_t)box_rows};
    cuuint32_t es[2] = {1, 1};
    fn(m, CU_TENSOR_MAP_DATA_TYPE_BFLOAT16, 2, const_cast<void*>(ptr), dims, strides, box, es, CU_TENSOR_MAP_INTERLEAVE_NONE,
       CU_TENSOR_MAP_SWIZZLE_128B, CU_TENSOR_MAP_L2_PROMOTION_L2_256B, CU_TENSOR_MAP_FLOAT_OOB_FILL_NONE);
}

static void make_tmap(EncodeFn fn, CUtensorMap* m, void* ptr) {
    cuuint64_t dims[2] = {512, (cuuint64_t)NN};
    cuuint64_t strides[1] = {1024};
    cuuint32_t box[2] = {64, 40};
    cuuint32_t es[2] = {1, 1};
    fn(m, CU_TENSOR_MAP_DATA_TYPE_BFLOAT16, 2, ptr, dims, strides, box, es, CU_TENSOR_MAP_INTERLEAVE_NONE,
       CU_TENSOR_MAP_SWIZZLE_128B, CU_TENSOR_MAP_L2_PROMOTION_NONE, CU_TENSOR_MAP_FLOAT_OOB_FILL_NONE);
}

static void make_smap(EncodeFn fn, CUtensorMap* m, void* ptr) {
    cuuint64_t dims[3] = {32, (cuuint64_t)NT, (cuuint64_t)NT};
    cuuint64_t strides[2] = {128, (cuuint64_t)NT * 128};
    cuuint32_t box[3] = {32, 1, (cuuint32_t)NT};
    cuuint32_t es[3] = {1, 1, 1};
    fn(m, CU_TENSOR_MAP_DATA_TYPE_UINT32, 3, ptr, dims, strides, box, es, CU_TENSOR_MAP_INTERLEAVE_NONE,
       CU_TENSOR_MAP_SWIZZLE_NONE, CU_TENSOR_MAP_L2_PROMOTION_NONE, CU_TENSOR_MAP_FLOAT_OOB_FILL_NONE);
}

static void make_wmap(EncodeFn fn, CUtensorMap* m, const void* ptr, int rows, int box_rows) {
    cuuint64_t dims[3] = {64, (cuuint64_t)rows, 4};
    cuuint64_t strides[2] = {(cuuint64_t)DD * 2, 128};
    cuuint32_t box[3] = {64, (cuuint32_t)box_rows, 4};
    cuuint32_t es[3] = {1, 1, 1};
    fn(m, CU_TENSOR_MAP_DATA_TYPE_BFLOAT16, 3, const_cast<void*>(ptr), dims, strides, box, es, CU_TENSOR_MAP_INTERLEAVE_NONE,
       CU_TENSOR_MAP_SWIZZLE_128B, CU_TENSOR_MAP_L2_PROMOTION_L2_256B, CU_TENSOR_MAP_FLOAT_OOB_FILL_NONE);
}

}

extern "C" void kernel_launch(void* const* d_in, const int* in_sizes, int n_in, void* d_out, int out_size) {
    using namespace egc;
    (void)in_sizes; (void)n_in; (void)out_size;
    static EncodeFn encode = nullptr;
    static void *p_tab = nullptr, *p_slots = nullptr, *p_bar = nullptr;
    if (!encode) {
        void* fn = nullptr;
        cudaDriverEntryPointQueryResult qr;
        cudaGetDriverEntryPoint("cuTensorMapEncodeTiled", &fn, cudaEnableDefault, &qr);
        encode = (EncodeFn)fn;
        cudaFuncSetAttribute(egc_kernel, cudaFuncAttributeMaxDynamicSharedMemorySize, SMEM_BYTES);
        cudaGetSymbolAddress(&p_tab, g_tab);
        cudaGetSymbolAddress(&p_slots, g_slots);
        cudaGetSymbolAddress(&p_bar, g_bar);
    }
    const __nv_bfloat16* x = (const __nv_bfloat16*)d_in[0];
    Params P;
    P.e_attr = (const __nv_bfloat16*)d_in[1];
    P.src = (const int*)d_in[2];
    P.dst = (const int*)d_in[3];
    P.u_w = (const __nv_bfloat16*)d_in[4];
    P.v_w = (const __nv_bfloat16*)d_in[5];
    P.g_w = (const __nv_bfloat16*)d_in[6];
    P.out = (__nv_bfloat16*)d_out;
    P.tab = (uint4*)p_tab;
    P.slots = (uint4*)p_slots;
    P.bar = (unsigned int*)p_bar;
    CUtensorMap tx, tg, tv, tu, tt, tc, ts;
    make_smap(encode, &ts, p_slots);
    make_tmap(encode, &tt, p_tab);
    make_map(encode, &tx, x, NN, TILE);
    make_wmap(encode, &tg, P.g_w, 2 * DD + 16, 64);
    make_wmap(encode, &tc, P.g_w, 2 * DD + 16, 16);
    make_wmap(encode, &tv, P.v_w, DD, 64);
    make_wmap(encode, &tu, P.u_w, DD, 64);
    egc_kernel<<<NT, NTHREADS, SMEM_BYTES, cudaStreamPerThread>>>(tx, tg, tv, tu, tt, tc, ts, P);
}
```

```cpp
#include <cuda_runtime.h>
#include <cuda_bf16.h>
#include <cuda.h>
#include <stdint.h>

namespace egc {

constexpr int NN = 10000;
constexpr int DD = 256;
constexpr int TILE = 80;
constexpr int NT = 125;
constexpr int EPC = 1280;
constexpr int NST = 3;
constexpr int NIT = 16;
#define EGC_HINT 20000
#define EGC_WAVE2 10
#define EGC_STQ 1
#define EGC_FULLLINE 1
#define EGC_META_LATE 0
#define EGC_OPAQUE 0
#define EGC_X_EARLY 2
constexpr int X_EARLY = EGC_X_EARLY;
constexpr int CAP_STEPS = 98;

constexpr int N_MAIN = 512, N_AUX = 128;
constexpr int NTHREADS = N_MAIN + N_AUX + 128;

constexpr int X_OFF = 0;
constexpr int RING_OFF = 40960;
constexpr int CT_OFF = RING_OFF + 32768;
constexpr int PARK_U = 0;
constexpr int PARK_XA = 40960;
constexpr int YB_OFF = 81920;
constexpr int EATTR_OFF = RING_OFF + NST * 32768;
constexpr int CAND_OFF = EATTR_OFF + CAP_STEPS * 512;
constexpr int MR_OFF = CAND_OFF + 16384;
constexpr int MQ_OFF = MR_OFF + (CAP_STEPS + 3) * 128;
constexpr int CAPG = 192;
constexpr int EL_OFF = MQ_OFF + CAP_STEPS * 32;
constexpr int ER_OFF = EL_OFF + 10 * CAPG * 4;
constexpr int CNT_OFF = ER_OFF + 10 * CAPG;
constexpr int MISC_OFF = CNT_OFF + 512;
constexpr int BAR_OFF = MISC_OFF + 128;
constexpr int SMEM_BYTES = BAR_OFF + 128;
static_assert(YB_OFF + 14 * 4096 <= EATTR_OFF, "park area and gather buffers must fit in x + ring");
static_assert(SMEM_BYTES <= 232448, "too much shared memory");

constexpr uint32_t REC_INV = 0x7FFFFFFFu, REC_OVF = 0x7E000000u;
__device__ __forceinline__ uint32_t rec_dl(uint32_t w) { return (w >> 24) & 127; }
constexpr uint32_t DBF_INV = 0x4380u;

constexpr int BAR_AUX = 1, BAR_MAIN = 2, BAR_READY = 3, BAR_CONSUMED = 4, BAR_TABLE = 5, BAR_GO = 6, BAR_S1 = 7, BAR_STG = 8, BAR_XFREE = 9, BAR_META = 10;

__device__ uint4 g_tab[(size_t)NN * 64];
__device__ float4 g_part[(size_t)NT * 160 * 32];
__device__ uint4 g_slots[(size_t)NT * NT * 8];
__device__ unsigned int g_bar[64];
#define PROF(i) do { } while (0)
#define PROF2(i) do { } while (0)

__device__ __forceinline__ void bar_sync(int id, int n) { asm volatile("bar.sync %0, %1;" ::"r"(id), "r"(n) : "memory"); }
__device__ __forceinline__ void bar_arrive(int id, int n) { asm volatile("bar.arrive %0, %1;" ::"r"(id), "r"(n) : "memory"); }

__device__ __forceinline__ void mbar_init(uint32_t bar, uint32_t cnt) {
    asm volatile("mbarrier.init.shared::cta.b64 [%0], %1;" ::"r"(bar), "r"(cnt) : "memory");
}
__device__ __forceinline__ void mbar_expect_tx(uint32_t bar, uint32_t bytes) {
    asm volatile("mbarrier.arrive.expect_tx.shared::cta.b64 _, [%0], %1;" ::"r"(bar), "r"(bytes) : "memory");
}
__device__ __forceinline__ void mbar_arrive(uint32_t bar) {
    asm volatile("mbarrier.arrive.shared::cta.b64 _, [%0];" ::"r"(bar) : "memory");
}
__device__ __forceinline__ void mbar_wait(uint32_t bar, uint32_t parity) {
    uint32_t ok;
    int spins = 0;
    do {
        asm volatile("{\n.reg .pred p;\nmbarrier.try_wait.parity.shared::cta.b64 p, [%1], %2, %3;\nselp.u32 %0, 1, 0, p;\n}"
                     : "=r"(ok) : "r"(bar), "r"(parity), "r"(EGC_HINT) : "memory");
    } while (!ok && ++spins < (1 << 16));
}
__device__ __forceinline__ void tma_2d(uint32_t dst, const CUtensorMap* map, int c0, int c1, uint32_t bar) {
    asm volatile("cp.async.bulk.tensor.2d.shared::cluster.global.mbarrier::complete_tx::bytes [%0], [%1, {%3, %4}], [%2];"
                 ::"r"(dst), "l"(map), "r"(bar), "r"(c0), "r"(c1) : "memory");
}
__device__ __forceinline__ void tma_3d(uint32_t dst, const CUtensorMap* map, int c0, int c1, int c2, uint32_t bar) {
    asm volatile("cp.async.bulk.tensor.3d.shared::cluster.global.mbarrier::complete_tx::bytes [%0], [%1, {%3, %4, %5}], [%2];"
                 ::"r"(dst), "l"(map), "r"(bar), "r"(c0), "r"(c1), "r"(c2) : "memory");
}
__device__ __forceinline__ void cp_async16(uint32_t dst, const void* src) {
    asm volatile("cp.async.cg.shared.global [%0], [%1], 16;" ::"r"(dst), "l"(src) : "memory");
}
__device__ __forceinline__ void cp_async16_if(bool p, uint32_t dst, const void* src) {
    asm volatile("{\n.reg .pred p;\nsetp.ne.u32 p, %2, 0;\n@p cp.async.cg.shared.global [%0], [%1], 16;\n}" ::"r"(dst), "l"(src), "r"((uint32_t)p) : "memory");
}
__device__ __forceinline__ void sts32_if(bool p, uint32_t a, uint32_t v) {
    asm volatile("{\n.reg .pred p;\nsetp.ne.u32 p, %2, 0;\n@p st.shared.u32 [%0], %1;\n}" ::"r"(a), "r"(v), "r"((uint32_t)p) : "memory");
}
__device__ __forceinline__ void sts16_if(bool p, uint32_t a, uint32_t v) {
    asm volatile("{\n.reg .pred p;\nsetp.ne.u32 p, %2, 0;\n@p st.shared.u16 [%0], %1;\n}" ::"r"(a), "h"((uint16_t)v), "r"((uint32_t)p) : "memory");
}
__device__ __forceinline__ void sts8_if(bool p, uint32_t a, uint32_t v) {
    asm volatile("{\n.reg .pred p;\nsetp.ne.u32 p, %2, 0;\n@p st.shared.u8 [%0], %1;\n}" ::"r"(a), "r"(v), "r"((uint32_t)p) : "memory");
}
__device__ __forceinline__ void cp_async_wait_all() { asm volatile("cp.async.wait_all;" ::: "memory"); }

__device__ __forceinline__ uint32_t lds32(uint32_t a) { uint32_t v; asm volatile("ld.shared.u32 %0, [%1];" : "=r"(v) : "r"(a)); return v; }
__device__ __forceinline__ uint2 lds64(uint32_t a) { uint2 v; asm volatile("ld.shared.v2.u32 {%0,%1}, [%2];" : "=r"(v.x), "=r"(v.y) : "r"(a)); return v; }
__device__ __forceinline__ uint4 lds128(uint32_t a) {
    uint4 v; asm volatile("ld.shared.v4.u32 {%0,%1,%2,%3}, [%4];" : "=r"(v.x), "=r"(v.y), "=r"(v.z), "=r"(v.w) : "r"(a)); return v;
}
__device__ __forceinline__ void sts16(uint32_t a, uint32_t v) { asm volatile("st.shared.u16 [%0], %1;" ::"r"(a), "h"((uint16_t)v) : "memory"); }
__device__ __forceinline__ void sts32(uint32_t a, uint32_t v) { asm volatile("st.shared.u32 [%0], %1;" ::"r"(a), "r"(v) : "memory"); }
__device__ __forceinline__ void sts128(uint32_t a, uint4 v) {
    asm volatile("st.shared.v4.u32 [%0], {%1,%2,%3,%4};" ::"r"(a), "r"(v.x), "r"(v.y), "r"(v.z), "r"(v.w) : "memory");
}
__device__ __forceinline__ uint32_t pack_bf16(float lo, float hi) {
    uint32_t d; asm("cvt.rn.bf16x2.f32 %0, %1, %2;" : "=r"(d) : "f"(hi), "f"(lo)); return d;
}
__device__ __forceinline__ uint32_t seteq_bf16x2(uint32_t a, uint32_t b) {
    uint32_t d; asm("set.eq.bf16x2.bf16x2 %0, %1, %2;" : "=r"(d) : "r"(a), "r"(b)); return d;
}
__device__ __forceinline__ uint32_t fma_bf16x2(uint32_t a, uint32_t b, uint32_t c) {
    uint32_t d; asm("fma.rn.bf16x2 %0, %1, %2, %3;" : "=r"(d) : "r"(a), "r"(b), "r"(c)); return d;
}
__device__ __forceinline__ float tanh_approx(float x) { float y; asm("tanh.approx.f32 %0, %1;" : "=f"(y) : "f"(x)); return y; }
__device__ __forceinline__ uint32_t bf16_bits_of_int(int v) { return __float_as_uint((float)v) >> 16; }

__device__ __forceinline__ void mma_bf16(float (&d)[4], uint32_t a0, uint32_t a1, uint32_t a2, uint32_t a3,
                                         uint32_t b0, uint32_t b1, float c0, float c1, float c2, float c3) {
    asm("mma.sync.aligned.m16n8k16.row.col.f32.bf16.bf16.f32 {%0,%1,%2,%3}, {%4,%5,%6,%7}, {%8,%9}, {%10,%11,%12,%13};"
        : "=f"(d[0]), "=f"(d[1]), "=f"(d[2]), "=f"(d[3])
        : "r"(a0), "r"(a1), "r"(a2), "r"(a3), "r"(b0), "r"(b1), "f"(c0), "f"(c1), "f"(c2), "f"(c3));
}

__device__ __forceinline__ void mma_bf16_k8(float (&d)[4], uint32_t a0, uint32_t a1, uint32_t b0) {
    asm("mma.sync.aligned.m16n8k8.row.col.f32.bf16.bf16.f32 {%0,%1,%2,%3}, {%4,%5}, {%6}, {%0,%1,%2,%3};"
        : "+f"(d[0]), "+f"(d[1]), "+f"(d[2]), "+f"(d[3]) : "r"(a0), "r"(a1), "r"(b0));
}

__device__ __forceinline__ void wgmma_n80(float (&d)[40], uint64_t da, uint64_t db, int scale_d) {
    asm volatile(
        "{\n.reg .pred p;\nsetp.ne.b32 p, %42, 0;\n"
        "wgmma.mma_async.sync.aligned.m64n80k16.f32.bf16.bf16 "
        "{%0,%1,%2,%3,%4,%5,%6,%7,%8,%9,%10,%11,%12,%13,%14,%15,%16,%17,%18,%19,"
        "%20,%21,%22,%23,%24,%25,%26,%27,%28,%29,%30,%31,%32,%33,%34,%35,%36,%37,%38,%39}, "
        "%40, %41, p, 1, 1, 1, 0;\n}"
        : "+f"(d[0]), "+f"(d[1]), "+f"(d[2]), "+f"(d[3]), "+f"(d[4]), "+f"(d[5]), "+f"(d[6]), "+f"(d[7]),
          "+f"(d[8]), "+f"(d[9]), "+f"(d[10]), "+f"(d[11]), "+f"(d[12]), "+f"(d[13]), "+f"(d[14]), "+f"(d[15]),
          "+f"(d[16]), "+f"(d[17]), "+f"(d[18]), "+f"(d[19]), "+f"(d[20]), "+f"(d[21]), "+f"(d[22]), "+f"(d[23]),
          "+f"(d[24]), "+f"(d[25]), "+f"(d[26]), "+f"(d[27]), "+f"(d[28]), "+f"(d[29]), "+f"(d[30]), "+f"(d[31]),
          "+f"(d[32]), "+f"(d[33]), "+f"(d[34]), "+f"(d[35]), "+f"(d[36]), "+f"(d[37]), "+f"(d[38]), "+f"(d[39])
        : "l"(da), "l"(db), "r"(scale_d));
}
__device__ __forceinline__ void wgmma_fence() { asm volatile("wgmma.fence.sync.aligned;" ::: "memory"); }
__device__ __forceinline__ void wgmma_commit() { asm volatile("wgmma.commit_group.sync.aligned;" ::: "memory"); }
template <int N> __device__ __forceinline__ void wgmma_wait() { asm volatile("wgmma.wait_group.sync.aligned %0;" ::"n"(N) : "memory"); }

__device__ __forceinline__ uint64_t smem_desc(uint32_t addr) {
    return (uint64_t)((addr & 0x3FFFF) >> 4) | ((uint64_t)1 << 16) | ((uint64_t)64 << 32) | ((uint64_t)1 << 62);
}

__device__ __forceinline__ unsigned int grid_target(const unsigned int* ctr) {
    unsigned int v;
    asm volatile("ld.relaxed.gpu.global.u32 %0, [%1];" : "=r"(v) : "l"(ctr) : "memory");
    return (v / NT + 1u) * NT;
}
__device__ __forceinline__ void grid_arrive(unsigned int* ctr) {
    asm volatile("red.release.gpu.global.add.u32 [%0], 1;" ::"l"(ctr) : "memory");
}
__device__ __forceinline__ void grid_arrive_relaxed(unsigned int* ctr) {
    asm volatile("red.relaxed.gpu.global.add.u32 [%0], 1;" ::"l"(ctr) : "memory");
}
__device__ __forceinline__ void grid_wait(const unsigned int* ctr, unsigned int target) {
    unsigned int v;
    int spins = 0;
    do {
        asm volatile("ld.acquire.gpu.global.u32 %0, [%1];" : "=r"(v) : "l"(ctr) : "memory");
    } while ((int)(v - target) < 0 && ++spins < (1 << 21));
}

constexpr int GCNT = MISC_OFF + 64;

__device__ __forceinline__ uint32_t bin_rank(uint32_t sb, uint32_t w) {
    uint32_t rank;
    asm volatile("{\n.reg .pred p;\nsetp.lt.u32 p, %1, %3;\nmov.u32 %0, 0xFFFF;\n@p atom.shared.add.u32 %0, [%2], 1;\n}"
                 : "=r"(rank) : "r"(w >> 24), "r"(sb + GCNT + ((w >> 25) & 0x3C)), "n"(TILE) : "memory");
    return rank;
}
__device__ __forceinline__ void bin_store(uint32_t sb, uint32_t w, uint32_t rank, uint32_t row) {
    const uint32_t idx = (w >> 27) * CAPG + rank;
    sts32_if(rank < CAPG, sb + EL_OFF + idx * 4, w);
    sts8_if(rank < CAPG, sb + ER_OFF + idx, row);
}
__device__ __forceinline__ bool bar_or(int id, int n, bool v) {
    uint32_t r;
    asm volatile("{\n.reg .pred p, q;\nsetp.ne.u32 q, %3, 0;\nbarrier.cta.red.or.pred p, %1, %2, q;\nselp.u32 %0, 1, 0, p;\n}"
                 : "=r"(r) : "r"(id), "r"(n), "r"((uint32_t)v) : "memory");
    return r;
}

__device__ __forceinline__ int layout_list(uint32_t sb, int t, int last) {
    int tot[10];
    {
        const uint4 a = lds128(sb + GCNT), b = lds128(sb + GCNT + 16);
        const uint2 c = lds64(sb + GCNT + 32);
        tot[0] = a.x; tot[1] = a.y; tot[2] = a.z; tot[3] = a.w; tot[4] = b.x; tot[5] = b.y; tot[6] = b.z; tot[7] = b.w;
        tot[8] = c.x; tot[9] = c.y;
    }
    int run = 0, myend = 0, gap = 0, tab = 0, mx = 0;
#pragma unroll
    for (int g = 0; g < 10; g++) {
        const int ge = run + ((tot[g] + 15) & ~15);
        const int off = t * 16 - run;
        if (off >= 0 && t * 16 < ge) tab = ((g * CAPG + off) << 16) | (tot[g] - off);
        if (g == t) myend = ge;
        if (g == 4) gap = ge;
        mx = max(mx, tot[g]);
        run = ge + (g == 4 ? 48 : 0);
    }
    if (mx > CAPG || run > CAP_STEPS * 16) return -1;
    if (t < CAP_STEPS) sts32(sb + CNT_OFF + t * 4, tab);
    if (t < 48) sts32(sb + MR_OFF + ((run >> 4) + (t >> 4)) * 128 + ((t & 15) >> 1) * 16 + (t & 1) * 4, 0xFFFFFFFFu);
    if (t < 10) sts32(sb + MISC_OFF + t * 4, myend >> 4);
    if (t == 10) sts32(sb + MISC_OFF + 40, (gap >> 4) + 3);
    if (t == 11) sts32(sb + MISC_OFF + 44, last);
    return run;
}

__device__ __forceinline__ void expand_meta(uint32_t sb, int t, int run) {
#pragma unroll 2
    for (int pos = t; pos < run; pos += N_AUX) {
        const uint32_t tb = lds32(sb + CNT_OFF + (pos >> 4) * 4);
        const int k = pos & 15, st16 = pos & ~15;
        const bool v = k < (int)(tb & 0xFFFF);
        const uint32_t idx = v ? (tb >> 16) + k : 0;
        const uint32_t w = lds32(sb + EL_OFF + idx * 4);
        uint32_t row;
        asm volatile("ld.shared.u8 %0, [%1];" : "=r"(row) : "r"(sb + ER_OFF + idx));
        const uint32_t se = w & 0xFFFFFF, sn = se / EPC;
        const uint32_t dbf = v ? bf16_bits_of_int((w >> 24) & 7) : DBF_INV;
        const uint32_t mr = sb + MR_OFF + st16 * 8 + (k & 7) * 16 + (k >> 3) * 4;
        sts32(mr, v ? sn : 0xFFFFFFFFu);
        sts32(mr + 8, dbf * 0x10001u);
        sts16(sb + MQ_OFF + (st16 + ((k & 7) >> 1) * 4 + (k & 1) + 2 * (k >> 3)) * 2, dbf);
        sts32(sb + CAND_OFF + pos * 4, v ? ((row - sn) * EPC + se) * 32 : 0xFFFFFFFFu);
    }
}

__device__ __forceinline__ void gather_attr(uint32_t sb, int t, int run, const __nv_bfloat16* __restrict__ e_attr) {
    const int h = t & 1, p0 = t >> 1;
    const char* base = (const char*)e_attr + h * 16;
    uint32_t src = sb + CAND_OFF + p0 * 4;
    uint32_t dst = sb + EATTR_OFF + p0 * 32 + ((h ^ ((p0 >> 2) & 1)) << 4);
#pragma unroll 1
    for (int pos = p0; pos < run; pos += 4 * 64) {
        uint32_t off[4];
#pragma unroll
        for (int i = 0; i < 4; i++) off[i] = lds32(src + i * 256);
#pragma unroll
        for (int i = 0; i < 4; i++) {
            if (pos + i * 64 < run)
                asm volatile("{\n.reg .pred p;\n.reg .b32 n, o;\n.reg .b64 a;\nsetp.ne.u32 p, %1, 0xFFFFFFFF;\nselp.b32 n, 16, 0, p;\n"
                             "selp.b32 o, %1, 0, p;\ncvt.u64.u32 a, o;\nadd.u64 a, a, %2;\ncp.async.cg.shared.global [%0], [a], 16, n;\n}"
                             ::"r"(dst + i * 2048), "r"(off[i]), "l"(base) : "memory");
        }
        src += 1024;
        dst += 8192;
    }
    if (t == 0) PROF2(113);
    cp_async_wait_all();
    if (t == 0) PROF2(114);
}

struct Params {
    const __nv_bfloat16* e_attr;
    const int* src;
    const int* dst;
    const __nv_bfloat16* g_w;
    const __nv_bfloat16* v_w;
    const __nv_bfloat16* u_w;
    __nv_bfloat16* out;
    uint4* tab;
    uint4* slots;
    unsigned int* bar;
    float4* part;
};

__global__ void __launch_bounds__(NTHREADS, 1)
egc_kernel(const __grid_constant__ CUtensorMap tm_x, const __grid_constant__ CUtensorMap tm_g,
           const __grid_constant__ CUtensorMap tm_v, const __grid_constant__ CUtensorMap tm_u,
           const __grid_constant__ CUtensorMap tm_t, const __grid_constant__ CUtensorMap tm_c,
           const __grid_constant__ CUtensorMap tm_s, const __grid_constant__ CUtensorMap tm_s2,
           const __grid_constant__ Params P) {
    extern __shared__ __align__(1024) unsigned char smem_raw[];
    const uint32_t sb = (uint32_t)__cvta_generic_to_shared(smem_raw);
    if (sb & 1023u) __trap();
    const int tid = threadIdx.x, warp = tid >> 5, lane = tid & 31;
    const int tile = blockIdx.x;
    const uint32_t bar_full = sb + BAR_OFF, bar_empty = bar_full + 8 * NST, bar_x = bar_empty + 8 * NST, bar_idx = bar_x + 32, bar_c = bar_idx + 8, bar_cand = bar_c + 8;
    const __nv_bfloat16* __restrict__ e_attr = P.e_attr;

    int4 dv, sv;
    if (warp < 16) {
        if (tid < EPC / 4) {
            asm volatile("ld.global.nc.v4.s32 {%0,%1,%2,%3}, [%4];" : "=r"(dv.x), "=r"(dv.y), "=r"(dv.z), "=r"(dv.w)
                         : "l"((const int4*)P.dst + tile * (EPC / 4) + tid));
            asm volatile("ld.global.nc.v4.s32 {%0,%1,%2,%3}, [%4];" : "=r"(sv.x), "=r"(sv.y), "=r"(sv.z), "=r"(sv.w)
                         : "l"((const int4*)P.src + tile * (EPC / 4) + tid));
        }
        sts128(sb + CAND_OFF + tid * 16, make_uint4(REC_INV, REC_INV, REC_INV, REC_INV));
        sts128(sb + CAND_OFF + (tid + 512) * 16, make_uint4(REC_INV, REC_INV, REC_INV, REC_INV));
        if (tid < 128) sts32(sb + CNT_OFF + tid * 4, 0);
        if (tid == 0) { PROF(0); PROF2(64); }
    } else if (warp < 20) {
        if (tid < N_MAIN + 18) sts32(sb + GCNT - 8 + (tid - N_MAIN) * 4, 0);
    } else if (tid == 640) {
        asm volatile("prefetch.tensormap [%0];" ::"l"(&tm_g) : "memory");
#pragma unroll
        for (int s = 0; s < NST; s++) {
            mbar_init(bar_full + 8 * s, 1);
            mbar_init(bar_empty + 8 * s, 16);
        }
        asm volatile("fence.mbarrier_init.release.cluster;" ::: "memory");
#pragma unroll 1
        for (int it = 0; it < NST; it++) {
            mbar_expect_tx(bar_full + 8 * it, 32768);
            tma_3d(sb + RING_OFF + it * 32768, &tm_g, 0, 256 + it * 64, 0, bar_full + 8 * it);
        }
    } else if (tid == 704) {
        asm volatile("prefetch.tensormap [%0];" ::"l"(&tm_x) : "memory");
#pragma unroll
        for (int s = 0; s < 4; s++) mbar_init(bar_x + 8 * s, 1);
        mbar_init(bar_idx, EPC / 128);
        mbar_init(bar_c, 1);
        mbar_init(bar_cand, 1);
        asm volatile("fence.mbarrier_init.release.cluster;" ::: "memory");
#pragma unroll 1
        for (int c = 0; c < X_EARLY; c++) {
            mbar_expect_tx(bar_x + 8 * c, 10240);
            tma_2d(sb + X_OFF + c * 10240, &tm_x, c * 64, tile * TILE, bar_x + 8 * c);
        }
    } else if (tid == 672) {
        asm volatile("prefetch.tensormap [%0];" ::"l"(&tm_v) : "memory");
        asm volatile("prefetch.tensormap [%0];" ::"l"(&tm_u) : "memory");
        asm volatile("prefetch.tensormap [%0];" ::"l"(&tm_t) : "memory");
        asm volatile("prefetch.tensormap [%0];" ::"l"(&tm_c) : "memory");
        asm volatile("prefetch.tensormap [%0];" ::"l"(&tm_s) : "memory");
        asm volatile("prefetch.tensormap [%0];" ::"l"(&tm_s2) : "memory");
        const int go = tile * 2176, vo = tile * 1056;
        const int gn = min(2176, 528 * 512 - go), vn = min(1056, 256 * 512 - vo);
        if (gn > 0) asm volatile("cp.async.bulk.prefetch.L2.global [%0], %1;" ::"l"((const char*)P.g_w + go), "r"(gn) : "memory");
        if (vn > 0) {
            asm volatile("cp.async.bulk.prefetch.L2.global [%0], %1;" ::"l"((const char*)P.v_w + vo), "r"(vn) : "memory");
            asm volatile("cp.async.bulk.prefetch.L2.global [%0], %1;" ::"l"((const char*)P.u_w + vo), "r"(vn) : "memory");
        }
    }
    __syncthreads();

    if (warp >= 20) {
        asm volatile("setmaxnreg.dec.sync.aligned.u32 24;");
        if (tid == 640) {
            int st = 0, par = 0;
#pragma unroll 1
            for (int it = NST; it < NIT; it++) {
                const int p = it >> 2;
                const CUtensorMap* m = (p == 1) ? &tm_v : (p == 3) ? &tm_u : &tm_g;
                const int row = ((p == 0) ? 256 : 0) + (it & 3) * 64;
                mbar_wait(bar_empty + 8 * st, par);
                mbar_expect_tx(bar_full + 8 * st, 32768);
                tma_3d(sb + RING_OFF + st * 32768, m, 0, row, 0, bar_full + 8 * st);
                if (++st == NST) { st = 0; par ^= 1; }
            }
            mbar_wait(bar_empty + 8 * 1, 0);
            mbar_expect_tx(bar_c, 8192);
            tma_3d(sb + CT_OFF, &tm_c, 0, 512, 0, bar_c);
        } else if (tid == 704) {
            if (X_EARLY < 4) mbar_wait(bar_idx, 0);
#pragma unroll 1
            for (int c = X_EARLY; c < 4; c++) {
                mbar_expect_tx(bar_x + 8 * c, 10240);
                tma_2d(sb + X_OFF + c * 10240, &tm_x, c * 64, tile * TILE, bar_x + 8 * c);
            }
        } else if (warp == 21) {
            mbar_wait(bar_x + 8 * 3, 0);
#pragma unroll 1
            for (int i = lane; i < EPC * 32 / 128; i += 32)
                asm volatile("prefetch.global.L2 [%0];" ::"l"((const char*)e_attr + (size_t)tile * EPC * 32 + i * 128) : "memory");
        } else if (warp == 23) {
            unsigned int target = 0;
            if (lane == 0) target = grid_target(P.bar);
#pragma unroll 1
            for (int wave = 0; wave < 2; wave++) {
                bar_sync(BAR_TABLE, N_MAIN + 32);
                if (lane == 0) {
#pragma unroll 1
                    for (int ds = 0; ds < 8; ds++) {
                        asm volatile("cp.async.bulk.tensor.2d.global.shared::cta.bulk_group [%0, {%2, %3}], [%1];"
                                     ::"l"(&tm_t), "r"(sb + EATTR_OFF + ds * 5120), "r"(ds * 64), "r"(tile * TILE + wave * 40) : "memory");
                        asm volatile("cp.async.bulk.commit_group;" ::: "memory");
                        asm volatile("cp.async.bulk.wait_group.read %0;" ::"n"(EGC_STQ) : "memory");
                    }
                    asm volatile("cp.async.bulk.wait_group.read 0;" ::: "memory");
                }
                __syncwarp();
                if (wave == 0) bar_arrive(BAR_STG, N_MAIN + 32);
                else bar_arrive(BAR_XFREE, N_AUX + 32);
            }
            if (lane == 0) {
                asm volatile("cp.async.bulk.wait_group 0;" ::: "memory");
                PROF(6);
                grid_arrive_relaxed(P.bar);
                grid_wait(P.bar, target);
                PROF(4);
            }
            __syncwarp();
            bar_arrive(BAR_GO, N_MAIN + 32);
        }
    } else if (warp >= 16) {
        asm volatile("setmaxnreg.dec.sync.aligned.u32 40;");
        const int t = tid - N_MAIN;
        unsigned int target = 0;
        if (t == 0) target = grid_target(P.bar + 32);
        bar_sync(BAR_S1, N_MAIN + N_AUX);
        if (t == 0) {
            PROF(1);
            asm volatile("cp.async.bulk.tensor.3d.global.shared::cta.bulk_group [%0, {%2, %3, %2}], [%1];"
                         ::"l"(&tm_s), "r"(sb + CAND_OFF), "r"(0), "r"(tile) : "memory");
            asm volatile("cp.async.bulk.commit_group;" ::: "memory");
            asm volatile("cp.async.bulk.wait_group 0;" ::: "memory");
            PROF(13);
            grid_arrive_relaxed(P.bar + 32);
            grid_wait(P.bar + 32, target);
            PROF(2); PROF2(99);
            asm volatile("fence.proxy.async.global;" ::: "memory");
            mbar_expect_tx(bar_cand, NT * 128);
            asm volatile("cp.async.bulk.tensor.4d.shared::cluster.global.mbarrier::complete_tx::bytes [%0], [%1, {%3, %3, %3, %4}], [%2];"
                         ::"r"(sb + CAND_OFF), "l"(&tm_s2), "r"(bar_cand), "r"(0), "r"(tile) : "memory");
        }
        const uint32_t row = sb + CAND_OFF + t * 32;
        mbar_wait(bar_cand, 0);
        if (t == 0) PROF2(100);
        bool ovf = false;
#pragma unroll 1
        for (int j = 0; j < 4; j++) {
            uint4 a = make_uint4(REC_INV, REC_INV, REC_INV, REC_INV), b = a;
            if (t < NT) { a = lds128(row + j * (NT * 32)); b = lds128(row + j * (NT * 32) + 16); }
            if (j >= 2 && !__any_sync(0xffffffffu, rec_dl(a.x) != 127)) break;
            const uint32_t rec[8] = {a.x, a.y, a.z, a.w, b.x, b.y, b.z, b.w};
            uint32_t rank[8];
#pragma unroll
            for (int i = 0; i < 8; i++) rank[i] = bin_rank(sb, rec[i]);
#pragma unroll
            for (int i = 0; i < 8; i++) bin_store(sb, rec[i], rank[i], t);
            ovf |= rec_dl(b.w) == 126;
        }
        if (t == 0) PROF2(101);
        ovf = bar_or(BAR_AUX, N_AUX, ovf);
        if (t == 0) { PROF(11); PROF2(105); }
        int run = ovf ? -1 : layout_list(sb, t, 1);
        if (run >= 0) {
            bar_sync(BAR_AUX, N_AUX);
            if (t == 0) PROF2(107);
            expand_meta(sb, t, run);
            if (t == 0) PROF2(108);
            bar_arrive(BAR_META, N_MAIN + N_AUX);
            bar_sync(BAR_AUX, N_AUX);
            bar_sync(BAR_XFREE, N_AUX + 32);
            if (t == 0) PROF2(111);
            gather_attr(sb, t, run, e_attr);
            if (t == 0) PROF(3);
            bar_arrive(BAR_READY, N_MAIN + N_AUX);
        } else {
            bar_sync(BAR_AUX, N_AUX);
            if (t < 16) sts32(sb + GCNT + t * 4, 0);
            bar_sync(BAR_AUX, N_AUX);
            bool first = true;
#pragma unroll 1
            for (int w0 = 0; w0 < NT * EPC; w0 += 128) {
                const int e = w0 + t, d = __ldg(P.dst + e), b = (unsigned)d / TILE;
                uint32_t w = REC_INV;
                const int c = (unsigned)e / EPC;
                if (b == tile) w = ((uint32_t)(d - b * TILE) << 24) | (__ldg(P.src + e) * EPC + (e - c * EPC));
                bin_store(sb, w, bin_rank(sb, w), c);
                bar_sync(BAR_AUX, N_AUX);
                int mx = 0, sum = 0;
#pragma unroll 1
                for (int g = 0; g < 10; g++) { const int v = lds32(sb + GCNT + g * 4); mx = max(mx, v); sum += v; }
                const bool fin = w0 + 128 >= NT * EPC;
                const bool flush = fin || mx > CAPG - 128 || sum > CAP_STEPS * 16 - 48 - 150 - 128;
                bar_sync(BAR_AUX, N_AUX);
                if (flush) {
                    if (first) bar_sync(BAR_XFREE, N_AUX + 32);
                    first = false;
                    run = layout_list(sb, t, fin);
                    bar_sync(BAR_AUX, N_AUX);
                    expand_meta(sb, t, run);
                    bar_arrive(BAR_META, N_MAIN + N_AUX);
                    bar_sync(BAR_AUX, N_AUX);
                    gather_attr(sb, t, run, e_attr);
                    bar_arrive(BAR_READY, N_MAIN + N_AUX);
                    if (!fin) bar_sync(BAR_CONSUMED, N_MAIN + N_AUX);
                    bar_sync(BAR_AUX, N_AUX);
                    if (t < 16) sts32(sb + GCNT + t * 4, 0);
                    bar_sync(BAR_AUX, N_AUX);
                }
            }
        }
    } else {
        asm volatile("setmaxnreg.inc.sync.aligned.u32 104;");
        const int wg = warp >> 2;
        const int r = lane >> 2, q = lane & 3;
        if (tid < EPC / 4) {
            const int dd[4] = {dv.x, dv.y, dv.z, dv.w};
            const int ss[4] = {sv.x, sv.y, sv.z, sv.w};
            uint32_t rank[4];
            int bb[4];
#pragma unroll
            for (int i = 0; i < 4; i++) {
                bb[i] = (unsigned)dd[i] / TILE;
                asm volatile("atom.shared.add.u32 %0, [%1], 1;" : "=r"(rank[i]) : "r"(sb + CNT_OFF + bb[i] * 4) : "memory");
            }
#pragma unroll
            for (int i = 0; i < 4; i++) {
                const uint32_t rec = ((uint32_t)(dd[i] - bb[i] * TILE) << 24) | (ss[i] * EPC + tid * 4 + i);
                sts32(sb + CAND_OFF + bb[i] * 128 + (min(rank[i], 31u) << 2), rank[i] < 31 ? rec : REC_OVF);
            }
            __syncwarp();
            if (lane == 0) mbar_arrive(bar_idx);
        }
        if (tid == 0) PROF(14);
        asm volatile("fence.proxy.async.shared::cta;" ::: "memory");
        bar_arrive(BAR_S1, N_MAIN + N_AUX);

        float d[40];
        uint32_t pB[20], pV[20], xa[20];
        const uint64_t da0 = smem_desc(sb + RING_OFF + wg * 8192), db0 = smem_desc(sb + X_OFF);

        auto stage = [&](const int it) {
            const int c = it & 3, st = it % NST;
            if (it < 4) mbar_wait(bar_x + 8 * c, 0);
            if (it == 0 && tid == 0) PROF(5);
            mbar_wait(bar_full + 8 * st, (it / NST) & 1);
            if (tid == 0) PROF2(it);
            wgmma_fence();
            const uint64_t da = da0 + st * 2048, db = db0 + c * 640;
            wgmma_n80(d, da, db, c != 0);
            wgmma_n80(d, da + 128, db + 2, 1);
            wgmma_n80(d, da + 256, db + 4, 1);
            wgmma_n80(d, da + 384, db + 6, 1);
            wgmma_commit();
        };
        auto release = [&](const int it) {
            if ((it + NST < NIT || it == 13) && lane == 0) mbar_arrive(bar_empty + 8 * (it % NST));
        };

        auto stage_table = [&](const int wave) {
            const uint32_t base = sb + EATTR_OFF + (warp >> 1) * 5120 + (lane & 7) * 128 +
                                  ((((warp & 1) * 4 + (lane >> 3)) ^ (lane & 7)) << 4);
#pragma unroll
            for (int jj = 0; jj < 5; jj++) {
                const int j = (wave * 5 + jj) * 2;
                asm volatile("stmatrix.sync.aligned.m8n8.x4.trans.shared.b16 [%0], {%1,%2,%3,%4};"
                             ::"r"(base + jj * 1024), "r"(pB[j]), "r"(pB[j + 1]), "r"(pV[j]), "r"(pV[j + 1]) : "memory");
            }
            asm volatile("fence.proxy.async.shared::cta;" ::: "memory");
            bar_arrive(BAR_TABLE, N_MAIN + 32);
        };
#pragma unroll
        for (int p = 0; p < 4; p++) {
#pragma unroll
            for (int c = 0; c < 4; c++) {
                stage(p * 4 + c);
                if (p == 2 && c == 0) {
                    stage_table(0);
                }
                if (p * 4 + c == EGC_WAVE2) { bar_sync(BAR_STG, N_MAIN + 32); stage_table(1); }
                if (c > 0) { wgmma_wait<1>(); release(p * 4 + c - 1); }
            }
            wgmma_wait<0>();
            release(p * 4 + 3);
            if (p == 0) {
#pragma unroll
                for (int j = 0; j < 20; j++) pB[j] = pack_bf16(0.5f * d[2 * j], 0.5f * d[2 * j + 1]);
            } else if (p == 1) {
#pragma unroll
                for (int j = 0; j < 20; j++) pV[j] = pack_bf16(0.5f * d[2 * j], 0.5f * d[2 * j + 1]);
            } else if (p == 2) {
#pragma unroll
                for (int j = 0; j < 20; j++) xa[j] = pack_bf16(0.5f * d[2 * j], 0.5f * d[2 * j + 1]);
            }
        }
        if (tid == 0) { PROF(7); PROF2(109); }

        uint32_t cf[2][4];
            mbar_wait(bar_c, 0);
#pragma unroll
            for (int c = 0; c < 2; c++) {
                const int k = (lane >> 4) * 8 + (lane & 7), col = (warp & 7) * 32 + c * 16 + ((lane >> 3) & 1) * 8;
                asm volatile("ldmatrix.sync.aligned.m8n8.x4.trans.shared.b16 {%0,%1,%2,%3}, [%4];"
                             : "=r"(cf[c][0]), "=r"(cf[c][1]), "=r"(cf[c][2]), "=r"(cf[c][3])
                             : "r"(sb + CT_OFF + (col >> 6) * 2048 + k * 128 + ((((col & 63) >> 3) ^ (k & 7)) << 4)));
#pragma unroll
                for (int i = 0; i < 4; i++)
                    asm("mul.rn.bf16x2 %0, %0, %1;" : "+r"(cf[c][i]) : "r"(0x3F003F00u));
            }
        bar_sync(BAR_MAIN, N_MAIN);
#pragma unroll
        for (int j = 0; j < 10; j++) {
            asm volatile("st.shared.v2.u32 [%0], {%1, %2};" ::"r"(sb + PARK_U + (warp * 10 + j) * 256 + lane * 8),
                         "r"(pack_bf16(d[4 * j], d[4 * j + 1])), "r"(pack_bf16(d[4 * j + 2], d[4 * j + 3])) : "memory");
            asm volatile("st.shared.v2.u32 [%0], {%1, %2};" ::"r"(sb + PARK_XA + (warp * 10 + j) * 256 + lane * 8), "r"(xa[2 * j]), "r"(xa[2 * j + 1]) : "memory");
        }
        bar_sync(BAR_MAIN, N_MAIN);

        {
            const int ds = warp & 7, set = warp >> 3;
            const uint32_t cA = bf16_bits_of_int(2 * q) | (bf16_bits_of_int(2 * q + 1) << 16);
            const uint32_t cB = bf16_bits_of_int(r) * 0x10001u;
            const uint32_t id0 = (r == 2 * q ? 0x00003F80u : 0u) | (r == 2 * q + 1 ? 0x3F800000u : 0u);
            const uint32_t id1 = EGC_OPAQUE ? lds32(sb + MISC_OFF + 56) : 0u, id2 = EGC_OPAQUE ? lds32(sb + MISC_OFF + 60) : 0u;
            const uint32_t id3 = EGC_OPAQUE ? id0 | id1 : id0;
            const char* tabl = (const char*)P.tab + ds * 128 + (lane & 7) * 16;
            const int ek = (lane >> 4) * 8 + (lane & 7);
            const uint32_t ea_l = sb + EATTR_OFF + ek * 32 + ((((lane >> 3) & 1) ^ ((ek >> 2) & 1)) << 4);
            const uint32_t mr_l = sb + MR_OFF + r * 16;
            const uint32_t mq_l = sb + MQ_OFF + q * 8;
            const uint32_t bounce = sb + CAND_OFF + warp * 512;
            const uint32_t pk = sb + (ds * 20 + set * 5) * 256 + lane * 8;
            float4* const part = P.part + ((size_t)tile * 160 + ds * 20 + set * 5) * 32 + lane;

            const uint32_t yb = warp < 14 ? sb + YB_OFF + warp * 4096 : sb + CAND_OFF + 8192 + (warp - 14) * 4096;
            const int g8 = lane >> 3;
            const uint32_t y_dst = yb + g8 * 128 + (((lane & 7) ^ g8) << 4);
            const uint32_t y_dst2 = yb + (g8 + 4) * 128 + (((lane & 7) ^ (g8 + 4)) << 4);
            const uint32_t mw_l = sb + MR_OFF + g8 * 16;
            const uint32_t y_ldb = yb + (lane & 7) * 128 + (((((lane >> 3) & 1) + (lane >> 4) * 4) ^ (lane & 7)) << 4);
            const uint32_t y_ldv = y_ldb ^ 32;

            auto gather1 = [&](uint32_t dst, uint32_t w) {
                asm volatile("{\n.reg .pred p;\n.reg .b64 a;\nsetp.ge.s32 p, %1, 0;\nmad.wide.u32 a, %1, 1024, %2;\n"
                             "@p cp.async.cg.shared.global [%0], [a], 16;\n}" ::"r"(dst), "r"(w), "l"(tabl) : "memory");
            };
            auto gather = [&](uint32_t dst, uint32_t w) {
                asm volatile("{\n.reg .pred p;\n.reg .b64 a;\nsetp.ge.s32 p, %2, 0;\nmad.wide.u32 a, %2, 1024, %3;\n"
                             "@p cp.async.cg.shared.global [%0], [a], 16;\n@p cp.async.cg.shared.global [%1], [a+64], 16;\n}"
                             ::"r"(dst), "r"(dst ^ 64), "r"(w), "l"(tabl) : "memory");
            };

            if (tid == 0) PROF2(110);
            bar_sync(BAR_GO, N_MAIN + 32);
            if (tid == 0) PROF2(112);
            for (int pass = 0;; pass++) {
                bar_sync(BAR_META, N_MAIN + N_AUX);
                const int last = lds32(sb + MISC_OFF + 44);
                int i = set ? (int)lds32(sb + MISC_OFF + 40) : 0;
                uint32_t pe = ea_l + i * 512, pr = mr_l + i * 128, pq = mq_l + i * 32;
                auto gather_step = [&](const int k, const int off) {
                    const uint32_t pw = pr - mr_l + mw_l + off;
                    const uint2 wa = lds64(pw), wb = lds64(pw + 64);
                    gather1(y_dst + k * 2048, wa.x);
                    gather1(y_dst2 + k * 2048, wb.x);
                    gather1(y_dst + k * 2048 + 1024, wa.y);
                    gather1(y_dst2 + k * 2048 + 1024, wb.y);
                    asm volatile("cp.async.commit_group;" ::: "memory");
                };
                {
#pragma unroll
                    for (int k = 0; k < 8; k++) sts128(yb + lane * 16 + k * 512, make_uint4(0, 0, 0, 0));
                    __syncwarp();
                    gather_step(0, 0);
                    gather_step(1, 128);
                }
                uint32_t xb[2][4], hv[2][4];
                auto fetch = [&](const int k, const int off) {
                    asm volatile("cp.async.wait_group 1;" ::: "memory");
                    __syncwarp();
#pragma unroll
                    for (int t = 0; t < 2; t++) {
                        asm volatile("ldmatrix.sync.aligned.m8n8.x4.shared.b16 {%0,%1,%2,%3}, [%4];"
                                     : "=r"(xb[t][0]), "=r"(xb[t][1]), "=r"(xb[t][2]), "=r"(xb[t][3]) : "r"(y_ldb + k * 2048 + t * 1024) : "memory");
                        asm volatile("ldmatrix.sync.aligned.m8n8.x4.trans.shared.b16 {%0,%1,%2,%3}, [%4];"
                                     : "=r"(hv[t][0]), "=r"(hv[t][1]), "=r"(hv[t][2]), "=r"(hv[t][3]) : "r"(y_ldv + k * 2048 + t * 1024) : "memory");
                    }
                    gather_step(k, off);
                };
                fetch(0, 2 * 128);
                bar_sync(BAR_READY, N_MAIN + N_AUX);
                if (tid == 0) { asm volatile("" ::: "memory"); PROF(8); PROF2(66); }
                int ph = 0;
                for (int g = 0; g < 5; g++) {
                    const int gend = lds32(sb + MISC_OFF + (set * 5 + g) * 4);
                    float acc[2][4];
                    uint2 xf[2];
#pragma unroll
                    for (int c = 0; c < 2; c++) {
                        if (pass == 0) {
                            const uint2 u = lds64(pk + PARK_U + (c * 10 + g) * 256);
                            acc[c][0] = __uint_as_float(u.x << 16); acc[c][1] = __uint_as_float(u.x & 0xFFFF0000u);
                            acc[c][2] = __uint_as_float(u.y << 16); acc[c][3] = __uint_as_float(u.y & 0xFFFF0000u);
                        } else {
                            const float4 a = part[(c * 10 + g) * 32];
                            acc[c][0] = a.x; acc[c][1] = a.y; acc[c][2] = a.z; acc[c][3] = a.w;
                        }
                        xf[c] = lds64(pk + PARK_XA + (c * 10 + g) * 256);
                    }

                    auto step = [&](const int k) {
                        const uint2 dd = lds64(pr + k * 128 + 8);
                        const uint2 db = lds64(pq + k * 32);
                        uint32_t e[4];
                        asm volatile("ldmatrix.sync.aligned.m8n8.x4.shared.b16 {%0,%1,%2,%3}, [%4];"
                                     : "=r"(e[0]), "=r"(e[1]), "=r"(e[2]), "=r"(e[3]) : "r"(pe + k * 512));
                        const uint32_t sa0 = seteq_bf16x2(dd.x, cA), sa1 = seteq_bf16x2(dd.y, cA);
                        const uint32_t sb0 = seteq_bf16x2(db.x, cB), sb1 = seteq_bf16x2(db.y, cB);
#pragma unroll
                        for (int c = 0; c < 2; c++) {
                            float p0[4], p1[4];
                            mma_bf16(p0, cf[c][0], cf[c][1], cf[c][2], cf[c][3], e[0], e[1], 0.f, 0.f, 0.f, 0.f);
                            mma_bf16(p1, cf[c][0], cf[c][1], cf[c][2], cf[c][3], e[2], e[3], 0.f, 0.f, 0.f, 0.f);
                            mma_bf16_k8(p0, xf[c].x, xf[c].y, sa0);
                            mma_bf16_k8(p1, xf[c].x, xf[c].y, sa1);
                            mma_bf16(p0, id0, id1, id2, id3, xb[0][2 * c], xb[0][2 * c + 1], p0[0], p0[1], p0[2], p0[3]);
                            mma_bf16(p1, id0, id1, id2, id3, xb[1][2 * c], xb[1][2 * c + 1], p1[0], p1[1], p1[2], p1[3]);
                            const uint32_t m0 = fma_bf16x2(hv[0][2 * c], pack_bf16(tanh_approx(p0[0]), tanh_approx(p0[1])), hv[0][2 * c]);
                            const uint32_t m1 = fma_bf16x2(hv[0][2 * c + 1], pack_bf16(tanh_approx(p0[2]), tanh_approx(p0[3])), hv[0][2 * c + 1]);
                            const uint32_t m2 = fma_bf16x2(hv[1][2 * c], pack_bf16(tanh_approx(p1[0]), tanh_approx(p1[1])), hv[1][2 * c]);
                            const uint32_t m3 = fma_bf16x2(hv[1][2 * c + 1], pack_bf16(tanh_approx(p1[2]), tanh_approx(p1[3])), hv[1][2 * c + 1]);
                            mma_bf16(acc[c], m0, m1, m2, m3, sb0, sb1, acc[c][0], acc[c][1], acc[c][2], acc[c][3]);
                        }
                        fetch(k ^ 1, (k + 3) * 128);
                    };

                    int rem = gend - i;
                    i = gend;
                    while (rem > 0) {
                        if (ph == 0) {
                            step(0);
                            ph = 1;
                            if (--rem == 0) break;
                        }
                        step(1);
                        ph = 0; pe += 2 * 512; pr += 2 * 128; pq += 2 * 32; --rem;
                    }

                    if (last) {
                        uint32_t o[4];
#pragma unroll
                        for (int c = 0; c < 2; c++) {
                            float z[4];
#pragma unroll
                            for (int j = 0; j < 4; j++) z[j] = __fdividef(acc[c][j], 1.f + __expf(-acc[c][j]));
                            o[2 * c] = pack_bf16(z[0], z[1]);
                            o[2 * c + 1] = pack_bf16(z[2], z[3]);
                        }
                        asm volatile("stmatrix.sync.aligned.m8n8.x4.trans.shared.b16 [%0], {%1,%2,%3,%4};"
                                     ::"r"(bounce + (lane & 7) * 64 + (((lane >> 3) ^ ((lane >> 1) & 3)) << 4)),
                                       "r"(o[0]), "r"(o[1]), "r"(o[2]), "r"(o[3]) : "memory");
                        __syncwarp();
                        const int node = lane >> 2;
                        const uint4 v = lds128(bounce + node * 64 + ((q ^ ((node >> 1) & 3)) << 4));
                        *(uint4*)(P.out + (size_t)(tile * TILE + (set * 5 + g) * 8 + node) * DD + ds * 32 + q * 8) = v;
                        __syncwarp();
                    } else {
#pragma unroll
                        for (int c = 0; c < 2; c++) part[(c * 10 + g) * 32] = make_float4(acc[c][0], acc[c][1], acc[c][2], acc[c][3]);
                    }
                }
                if (last) break;
                cp_async_wait_all();
                bar_arrive(BAR_CONSUMED, N_MAIN + N_AUX);
            }
            if (tid == 0) { PROF(9); PROF2(65); }
        }
    }
}

typedef CUresult (*EncodeFn)(CUtensorMap*, CUtensorMapDataType, cuuint32_t, void*, const cuuint64_t*, const cuuint64_t*,
                             const cuuint32_t*, const cuuint32_t*, CUtensorMapInterleave, CUtensorMapSwizzle,
                             CUtensorMapL2promotion, CUtensorMapFloatOOBfill);

static void make_map(EncodeFn fn, CUtensorMap* m, const void* ptr, int rows, int box_rows) {
    cuuint64_t dims[2] = {(cuuint64_t)DD, (cuuint64_t)rows};
    cuuint64_t strides[1] = {(cuuint64_t)DD * 2};
    cuuint32_t box[2] = {64, (cuuint32_t)box_rows};
    cuuint32_t es[2] = {1, 1};
    fn(m, CU_TENSOR_MAP_DATA_TYPE_BFLOAT16, 2, const_cast<void*>(ptr), dims, strides, box, es, CU_TENSOR_MAP_INTERLEAVE_NONE,
       CU_TENSOR_MAP_SWIZZLE_128B, CU_TENSOR_MAP_L2_PROMOTION_L2_256B, CU_TENSOR_MAP_FLOAT_OOB_FILL_NONE);
}

static void make_tmap(EncodeFn fn, CUtensorMap* m, void* ptr) {
    cuuint64_t dims[2] = {512, (cuuint64_t)NN};
    cuuint64_t strides[1] = {1024};
    cuuint32_t box[2] = {64, 40};
    cuuint32_t es[2] = {1, 1};
    fn(m, CU_TENSOR_MAP_DATA_TYPE_BFLOAT16, 2, ptr, dims, strides, box, es, CU_TENSOR_MAP_INTERLEAVE_NONE,
       CU_TENSOR_MAP_SWIZZLE_128B, CU_TENSOR_MAP_L2_PROMOTION_NONE, CU_TENSOR_MAP_FLOAT_OOB_FILL_NONE);
}

static void make_smap(EncodeFn fn, CUtensorMap* m, void* ptr) {
    cuuint64_t dims[3] = {32, (cuuint64_t)NT, (cuuint64_t)NT};
    cuuint64_t strides[2] = {128, (cuuint64_t)NT * 128};
    cuuint32_t box[3] = {32, 1, (cuuint32_t)NT};
    cuuint32_t es[3] = {1, 1, 1};
    fn(m, CU_TENSOR_MAP_DATA_TYPE_UINT32, 3, ptr, dims, strides, box, es, CU_TENSOR_MAP_INTERLEAVE_NONE,
       CU_TENSOR_MAP_SWIZZLE_NONE, CU_TENSOR_MAP_L2_PROMOTION_NONE, CU_TENSOR_MAP_FLOAT_OOB_FILL_NONE);
}

static void make_smap2(EncodeFn fn, CUtensorMap* m, void* ptr) {
    cuuint64_t dims[4] = {8, (cuuint64_t)NT, 4, (cuuint64_t)NT};
    cuuint64_t strides[3] = {128, 32, (cuuint64_t)NT * 128};
    cuuint32_t box[4] = {8, (cuuint32_t)NT, 4, 1};
    cuuint32_t es[4] = {1, 1, 1, 1};
    fn(m, CU_TENSOR_MAP_DATA_TYPE_UINT32, 4, ptr, dims, strides, box, es, CU_TENSOR_MAP_INTERLEAVE_NONE,
       CU_TENSOR_MAP_SWIZZLE_NONE, CU_TENSOR_MAP_L2_PROMOTION_NONE, CU_TENSOR_MAP_FLOAT_OOB_FILL_NONE);
}

static void make_wmap(EncodeFn fn, CUtensorMap* m, const void* ptr, int rows, int box_rows) {
    cuuint64_t dims[3] = {64, (cuuint64_t)rows, 4};
    cuuint64_t strides[2] = {(cuuint64_t)DD * 2, 128};
    cuuint32_t box[3] = {64, (cuuint32_t)box_rows, 4};
    cuuint32_t es[3] = {1, 1, 1};
    fn(m, CU_TENSOR_MAP_DATA_TYPE_BFLOAT16, 3, const_cast<void*>(ptr), dims, strides, box, es, CU_TENSOR_MAP_INTERLEAVE_NONE,
       CU_TENSOR_MAP_SWIZZLE_128B, CU_TENSOR_MAP_L2_PROMOTION_L2_256B, CU_TENSOR_MAP_FLOAT_OOB_FILL_NONE);
}

}

extern "C" void kernel_launch(void* const* d_in, const int* in_sizes, int n_in, void* d_out, int out_size) {
    using namespace egc;
    (void)in_sizes; (void)n_in; (void)out_size;
    static EncodeFn encode = nullptr;
    static void *p_tab = nullptr, *p_slots = nullptr, *p_bar = nullptr, *p_part = nullptr;
    if (!encode) {
        void* fn = nullptr;
        cudaDriverEntryPointQueryResult qr;
        cudaGetDriverEntryPoint("cuTensorMapEncodeTiled", &fn, cudaEnableDefault, &qr);
        encode = (EncodeFn)fn;
        cudaFuncSetAttribute(egc_kernel, cudaFuncAttributeMaxDynamicSharedMemorySize, SMEM_BYTES);
        cudaGetSymbolAddress(&p_tab, g_tab);
        cudaGetSymbolAddress(&p_slots, g_slots);
        cudaGetSymbolAddress(&p_bar, g_bar);
        cudaGetSymbolAddress(&p_part, g_part);
    }
    const __nv_bfloat16* x = (const __nv_bfloat16*)d_in[0];
    Params P;
    P.e_attr = (const __nv_bfloat16*)d_in[1];
    P.src = (const int*)d_in[2];
    P.dst = (const int*)d_in[3];
    P.u_w = (const __nv_bfloat16*)d_in[4];
    P.v_w = (const __nv_bfloat16*)d_in[5];
    P.g_w = (const __nv_bfloat16*)d_in[6];
    P.out = (__nv_bfloat16*)d_out;
    P.tab = (uint4*)p_tab;
    P.slots = (uint4*)p_slots;
    P.bar = (unsigned int*)p_bar;
    P.part = (float4*)p_part;
    CUtensorMap tx, tg, tv, tu, tt, tc, ts, ts2;
    make_smap(encode, &ts, p_slots);
    make_smap2(encode, &ts2, p_slots);
    make_tmap(encode, &tt, p_tab);
    make_map(encode, &tx, x, NN, TILE);
    make_wmap(encode, &tg, P.g_w, 2 * DD + 16, 64);
    make_wmap(encode, &tc, P.g_w, 2 * DD + 16, 16);
    make_wmap(encode, &tv, P.v_w, DD, 64);
    make_wmap(encode, &tu, P.u_w, DD, 64);
    egc_kernel<<<NT, NTHREADS, SMEM_BYTES, cudaStreamPerThread>>>(tx, tg, tv, tu, tt, tc, ts, ts2, P);
}
```

```cpp
#include <cuda_runtime.h>
#include <cuda_bf16.h>
#include <cuda.h>
#include <stdint.h>

namespace egc {

constexpr int NN = 10000;
constexpr int DD = 256;
constexpr int TILE = 80;
constexpr int NT = 125;
constexpr int EPC = 1280;
constexpr int NST = 3;
constexpr int NIT = 16;
constexpr int WAIT_HINT_NS = 20000;
constexpr int WAVE2_TILE = 10;
constexpr int STORE_QUEUE = 3;
constexpr int X_EARLY = 2;
constexpr int CAP_STEPS = 98;

constexpr int N_MAIN = 512, N_AUX = 128;
constexpr int NTHREADS = N_MAIN + N_AUX + 128;

constexpr int X_OFF = 0;
constexpr int RING_OFF = 40960;
constexpr int CT_OFF = RING_OFF + 32768;
constexpr int PARK_U = 0;
constexpr int PARK_XA = 40960;
constexpr int YB_OFF = 81920;
constexpr int EATTR_OFF = RING_OFF + NST * 32768;
constexpr int CAND_OFF = EATTR_OFF + CAP_STEPS * 512;
constexpr int MR_OFF = CAND_OFF + 16384;
constexpr int MQ_OFF = MR_OFF + (CAP_STEPS + 3) * 128;
constexpr int CAPG = 192;
constexpr int EL_OFF = MQ_OFF + CAP_STEPS * 32;
constexpr int ER_OFF = EL_OFF + 10 * CAPG * 4;
constexpr int CNT_OFF = ER_OFF + 10 * CAPG;
constexpr int MISC_OFF = CNT_OFF + 512;
constexpr int BAR_OFF = MISC_OFF + 128;
constexpr int SMEM_BYTES = BAR_OFF + 128;
static_assert(YB_OFF + 14 * 4096 <= EATTR_OFF, "park area and gather buffers must fit in x + ring");
static_assert(SMEM_BYTES <= 232448, "too much shared memory");

constexpr uint32_t REC_INV = 0x7FFFFFFFu, REC_OVF = 0x7E000000u;
__device__ __forceinline__ uint32_t rec_dl(uint32_t w) { return (w >> 24) & 127; }
constexpr uint32_t DBF_INV = 0x4380u;

constexpr int BAR_AUX = 1, BAR_MAIN = 2, BAR_READY = 3, BAR_CONSUMED = 4, BAR_TABLE = 5, BAR_GO = 6, BAR_S1 = 7, BAR_STG = 8, BAR_XFREE = 9, BAR_META = 10;

__device__ uint4 g_tab[(size_t)NN * 64];
__device__ float4 g_part[(size_t)NT * 160 * 32];
__device__ uint4 g_slots[(size_t)NT * NT * 8];
__device__ unsigned int g_bar[64];

__device__ __forceinline__ void bar_sync(int id, int n) { asm volatile("bar.sync %0, %1;" ::"r"(id), "r"(n) : "memory"); }
__device__ __forceinline__ void bar_arrive(int id, int n) { asm volatile("bar.arrive %0, %1;" ::"r"(id), "r"(n) : "memory"); }

__device__ __forceinline__ void mbar_init(uint32_t bar, uint32_t cnt) {
    asm volatile("mbarrier.init.shared::cta.b64 [%0], %1;" ::"r"(bar), "r"(cnt) : "memory");
}
__device__ __forceinline__ void mbar_expect_tx(uint32_t bar, uint32_t bytes) {
    asm volatile("mbarrier.arrive.expect_tx.shared::cta.b64 _, [%0], %1;" ::"r"(bar), "r"(bytes) : "memory");
}
__device__ __forceinline__ void mbar_arrive(uint32_t bar) {
    asm volatile("mbarrier.arrive.shared::cta.b64 _, [%0];" ::"r"(bar) : "memory");
}
__device__ __forceinline__ void mbar_wait(uint32_t bar, uint32_t parity) {
    uint32_t ok;
    int spins = 0;
    do {
        asm volatile("{\n.reg .pred p;\nmbarrier.try_wait.parity.shared::cta.b64 p, [%1], %2, %3;\nselp.u32 %0, 1, 0, p;\n}"
                     : "=r"(ok) : "r"(bar), "r"(parity), "r"(WAIT_HINT_NS) : "memory");
    } while (!ok && ++spins < (1 << 16));
}
__device__ __forceinline__ void tma_2d(uint32_t dst, const CUtensorMap* map, int c0, int c1, uint32_t bar) {
    asm volatile("cp.async.bulk.tensor.2d.shared::cluster.global.mbarrier::complete_tx::bytes [%0], [%1, {%3, %4}], [%2];"
                 ::"r"(dst), "l"(map), "r"(bar), "r"(c0), "r"(c1) : "memory");
}
__device__ __forceinline__ void tma_3d(uint32_t dst, const CUtensorMap* map, int c0, int c1, int c2, uint32_t bar) {
    asm volatile("cp.async.bulk.tensor.3d.shared::cluster.global.mbarrier::complete_tx::bytes [%0], [%1, {%3, %4, %5}], [%2];"
                 ::"r"(dst), "l"(map), "r"(bar), "r"(c0), "r"(c1), "r"(c2) : "memory");
}
__device__ __forceinline__ void sts32_if(bool p, uint32_t a, uint32_t v) {
    asm volatile("{\n.reg .pred p;\nsetp.ne.u32 p, %2, 0;\n@p st.shared.u32 [%0], %1;\n}" ::"r"(a), "r"(v), "r"((uint32_t)p) : "memory");
}
__device__ __forceinline__ void sts8_if(bool p, uint32_t a, uint32_t v) {
    asm volatile("{\n.reg .pred p;\nsetp.ne.u32 p, %2, 0;\n@p st.shared.u8 [%0], %1;\n}" ::"r"(a), "r"(v), "r"((uint32_t)p) : "memory");
}
__device__ __forceinline__ void cp_async_wait_all() { asm volatile("cp.async.wait_all;" ::: "memory"); }

__device__ __forceinline__ uint32_t lds32(uint32_t a) { uint32_t v; asm volatile("ld.shared.u32 %0, [%1];" : "=r"(v) : "r"(a)); return v; }
__device__ __forceinline__ uint2 lds64(uint32_t a) { uint2 v; asm volatile("ld.shared.v2.u32 {%0,%1}, [%2];" : "=r"(v.x), "=r"(v.y) : "r"(a)); return v; }
__device__ __forceinline__ uint4 lds128(uint32_t a) {
    uint4 v; asm volatile("ld.shared.v4.u32 {%0,%1,%2,%3}, [%4];" : "=r"(v.x), "=r"(v.y), "=r"(v.z), "=r"(v.w) : "r"(a)); return v;
}
__device__ __forceinline__ void sts16(uint32_t a, uint32_t v) { asm volatile("st.shared.u16 [%0], %1;" ::"r"(a), "h"((uint16_t)v) : "memory"); }
__device__ __forceinline__ void sts32(uint32_t a, uint32_t v) { asm volatile("st.shared.u32 [%0], %1;" ::"r"(a), "r"(v) : "memory"); }
__device__ __forceinline__ void sts128(uint32_t a, uint4 v) {
    asm volatile("st.shared.v4.u32 [%0], {%1,%2,%3,%4};" ::"r"(a), "r"(v.x), "r"(v.y), "r"(v.z), "r"(v.w) : "memory");
}
__device__ __forceinline__ uint32_t pack_bf16(float lo, float hi) {
    uint32_t d; asm("cvt.rn.bf16x2.f32 %0, %1, %2;" : "=r"(d) : "f"(hi), "f"(lo)); return d;
}
__device__ __forceinline__ uint32_t seteq_bf16x2(uint32_t a, uint32_t b) {
    uint32_t d; asm("set.eq.bf16x2.bf16x2 %0, %1, %2;" : "=r"(d) : "r"(a), "r"(b)); return d;
}
__device__ __forceinline__ uint32_t fma_bf16x2(uint32_t a, uint32_t b, uint32_t c) {
    uint32_t d; asm("fma.rn.bf16x2 %0, %1, %2, %3;" : "=r"(d) : "r"(a), "r"(b), "r"(c)); return d;
}
__device__ __forceinline__ float tanh_approx(float x) { float y; asm("tanh.approx.f32 %0, %1;" : "=f"(y) : "f"(x)); return y; }
__device__ __forceinline__ uint32_t bf16_bits_of_int(int v) { return __float_as_uint((float)v) >> 16; }

__device__ __forceinline__ void mma_bf16(float (&d)[4], uint32_t a0, uint32_t a1, uint32_t a2, uint32_t a3,
                                         uint32_t b0, uint32_t b1, float c0, float c1, float c2, float c3) {
    asm("mma.sync.aligned.m16n8k16.row.col.f32.bf16.bf16.f32 {%0,%1,%2,%3}, {%4,%5,%6,%7}, {%8,%9}, {%10,%11,%12,%13};"
        : "=f"(d[0]), "=f"(d[1]), "=f"(d[2]), "=f"(d[3])
        : "r"(a0), "r"(a1), "r"(a2), "r"(a3), "r"(b0), "r"(b1), "f"(c0), "f"(c1), "f"(c2), "f"(c3));
}

__device__ __forceinline__ void mma_bf16_k8(float (&d)[4], uint32_t a0, uint32_t a1, uint32_t b0) {
    asm("mma.sync.aligned.m16n8k8.row.col.f32.bf16.bf16.f32 {%0,%1,%2,%3}, {%4,%5}, {%6}, {%0,%1,%2,%3};"
        : "+f"(d[0]), "+f"(d[1]), "+f"(d[2]), "+f"(d[3]) : "r"(a0), "r"(a1), "r"(b0));
}

__device__ __forceinline__ void wgmma_n80(float (&d)[40], uint64_t da, uint64_t db, int scale_d) {
    asm volatile(
        "{\n.reg .pred p;\nsetp.ne.b32 p, %42, 0;\n"
        "wgmma.mma_async.sync.aligned.m64n80k16.f32.bf16.bf16 "
        "{%0,%1,%2,%3,%4,%5,%6,%7,%8,%9,%10,%11,%12,%13,%14,%15,%16,%17,%18,%19,"
        "%20,%21,%22,%23,%24,%25,%26,%27,%28,%29,%30,%31,%32,%33,%34,%35,%36,%37,%38,%39}, "
        "%40, %41, p, 1, 1, 1, 0;\n}"
        : "+f"(d[0]), "+f"(d[1]), "+f"(d[2]), "+f"(d[3]), "+f"(d[4]), "+f"(d[5]), "+f"(d[6]), "+f"(d[7]),
          "+f"(d[8]), "+f"(d[9]), "+f"(d[10]), "+f"(d[11]), "+f"(d[12]), "+f"(d[13]), "+f"(d[14]), "+f"(d[15]),
          "+f"(d[16]), "+f"(d[17]), "+f"(d[18]), "+f"(d[19]), "+f"(d[20]), "+f"(d[21]), "+f"(d[22]), "+f"(d[23]),
          "+f"(d[24]), "+f"(d[25]), "+f"(d[26]), "+f"(d[27]), "+f"(d[28]), "+f"(d[29]), "+f"(d[30]), "+f"(d[31]),
          "+f"(d[32]), "+f"(d[33]), "+f"(d[34]), "+f"(d[35]), "+f"(d[36]), "+f"(d[37]), "+f"(d[38]), "+f"(d[39])
        : "l"(da), "l"(db), "r"(scale_d));
}
__device__ __forceinline__ void wgmma_fence() { asm volatile("wgmma.fence.sync.aligned;" ::: "memory"); }
__device__ __forceinline__ void wgmma_commit() { asm volatile("wgmma.commit_group.sync.aligned;" ::: "memory"); }
template <int N> __device__ __forceinline__ void wgmma_wait() { asm volatile("wgmma.wait_group.sync.aligned %0;" ::"n"(N) : "memory"); }

__device__ __forceinline__ uint64_t smem_desc(uint32_t addr) {
    return (uint64_t)((addr & 0x3FFFF) >> 4) | ((uint64_t)1 << 16) | ((uint64_t)64 << 32) | ((uint64_t)1 << 62);
}

__device__ __forceinline__ unsigned int grid_target(const unsigned int* ctr) {
    unsigned int v;
    asm volatile("ld.relaxed.gpu.global.u32 %0, [%1];" : "=r"(v) : "l"(ctr) : "memory");
    return (v / NT + 1u) * NT;
}
__device__ __forceinline__ void grid_arrive_relaxed(unsigned int* ctr) {
    asm volatile("red.relaxed.gpu.global.add.u32 [%0], 1;" ::"l"(ctr) : "memory");
}
__device__ __forceinline__ void grid_wait(const unsigned int* ctr, unsigned int target) {
    unsigned int v;
    int spins = 0;
    do {
        asm volatile("ld.acquire.gpu.global.u32 %0, [%1];" : "=r"(v) : "l"(ctr) : "memory");
    } while ((int)(v - target) < 0 && ++spins < (1 << 21));
}

constexpr int GCNT = MISC_OFF + 64;

__device__ __forceinline__ uint32_t bin_rank(uint32_t sb, uint32_t w) {
    uint32_t rank;
    asm volatile("{\n.reg .pred p;\nsetp.lt.u32 p, %1, %3;\nmov.u32 %0, 0xFFFF;\n@p atom.shared.add.u32 %0, [%2], 1;\n}"
                 : "=r"(rank) : "r"(w >> 24), "r"(sb + GCNT + ((w >> 25) & 0x3C)), "n"(TILE) : "memory");
    return rank;
}
__device__ __forceinline__ void bin_store(uint32_t sb, uint32_t w, uint32_t rank, uint32_t row) {
    const uint32_t idx = (w >> 27) * CAPG + rank;
    sts32_if(rank < CAPG, sb + EL_OFF + idx * 4, w);
    sts8_if(rank < CAPG, sb + ER_OFF + idx, row);
}
__device__ __forceinline__ bool bar_or(int id, int n, bool v) {
    uint32_t r;
    asm volatile("{\n.reg .pred p, q;\nsetp.ne.u32 q, %3, 0;\nbarrier.cta.red.or.pred p, %1, %2, q;\nselp.u32 %0, 1, 0, p;\n}"
                 : "=r"(r) : "r"(id), "r"(n), "r"((uint32_t)v) : "memory");
    return r;
}

__device__ __forceinline__ int layout_list(uint32_t sb, int t, int last) {
    int tot[10];
    {
        const uint4 a = lds128(sb + GCNT), b = lds128(sb + GCNT + 16);
        const uint2 c = lds64(sb + GCNT + 32);
        tot[0] = a.x; tot[1] = a.y; tot[2] = a.z; tot[3] = a.w; tot[4] = b.x; tot[5] = b.y; tot[6] = b.z; tot[7] = b.w;
        tot[8] = c.x; tot[9] = c.y;
    }
    int run = 0, myend = 0, gap = 0, tab = 0, mx = 0;
#pragma unroll
    for (int g = 0; g < 10; g++) {
        const int ge = run + ((tot[g] + 15) & ~15);
        const int off = t * 16 - run;
        if (off >= 0 && t * 16 < ge) tab = ((g * CAPG + off) << 16) | (tot[g] - off);
        if (g == t) myend = ge;
        if (g == 4) gap = ge;
        mx = max(mx, tot[g]);
        run = ge + (g == 4 ? 48 : 0);
    }
    if (mx > CAPG || run > CAP_STEPS * 16) return -1;
    if (t < CAP_STEPS) sts32(sb + CNT_OFF + t * 4, tab);
    if (t < 48) sts32(sb + MR_OFF + ((run >> 4) + (t >> 4)) * 128 + ((t & 15) >> 1) * 16 + (t & 1) * 4, 0xFFFFFFFFu);
    if (t < 10) sts32(sb + MISC_OFF + t * 4, myend >> 4);
    if (t == 10) sts32(sb + MISC_OFF + 40, (gap >> 4) + 3);
    if (t == 11) sts32(sb + MISC_OFF + 44, last);
    return run;
}

__device__ __forceinline__ void expand_meta(uint32_t sb, int t, int run) {
#pragma unroll 2
    for (int pos = t; pos < run; pos += N_AUX) {
        const uint32_t tb = lds32(sb + CNT_OFF + (pos >> 4) * 4);
        const int k = pos & 15, st16 = pos & ~15;
        const bool v = k < (int)(tb & 0xFFFF);
        const uint32_t idx = v ? (tb >> 16) + k : 0;
        const uint32_t w = lds32(sb + EL_OFF + idx * 4);
        uint32_t row;
        asm volatile("ld.shared.u8 %0, [%1];" : "=r"(row) : "r"(sb + ER_OFF + idx));
        const uint32_t se = w & 0xFFFFFF, sn = se / EPC;
        const uint32_t dbf = v ? bf16_bits_of_int((w >> 24) & 7) : DBF_INV;
        const uint32_t mr = sb + MR_OFF + st16 * 8 + (k & 7) * 16 + (k >> 3) * 4;
        sts32(mr, v ? sn : 0xFFFFFFFFu);
        sts32(mr + 8, dbf * 0x10001u);
        sts16(sb + MQ_OFF + (st16 + ((k & 7) >> 1) * 4 + (k & 1) + 2 * (k >> 3)) * 2, dbf);
        sts32(sb + CAND_OFF + pos * 4, v ? ((row - sn) * EPC + se) * 32 : 0xFFFFFFFFu);
    }
}

__device__ __forceinline__ void gather_attr_range(uint32_t sb, int t, int p_begin, int p_end, const __nv_bfloat16* __restrict__ e_attr) {
    const int h = t & 1, p0 = p_begin + (t >> 1);
    const char* base = (const char*)e_attr + h * 16;
    uint32_t src = sb + CAND_OFF + p0 * 4;
    uint32_t dst = sb + EATTR_OFF + p0 * 32 + ((h ^ ((p0 >> 2) & 1)) << 4);
#pragma unroll 1
    for (int pos = p0; pos < p_end; pos += 2 * 64) {
        uint32_t off[2];
#pragma unroll
        for (int i = 0; i < 2; i++) off[i] = lds32(src + i * 256);
#pragma unroll
        for (int i = 0; i < 2; i++) {
            if (pos + i * 64 < p_end)
                asm volatile("{\n.reg .pred p;\n.reg .b32 n, o;\n.reg .b64 a;\nsetp.ne.u32 p, %1, 0xFFFFFFFF;\nselp.b32 n, 16, 0, p;\n"
                             "selp.b32 o, %1, 0, p;\ncvt.u64.u32 a, o;\nadd.u64 a, a, %2;\ncp.async.cg.shared.global [%0], [a], 16, n;\n}"
                             ::"r"(dst + i * 2048), "r"(off[i]), "l"(base) : "memory");
        }
        src += 512;
        dst += 4096;
    }
}
__device__ __forceinline__ void gather_attr(uint32_t sb, int t, int run, const __nv_bfloat16* __restrict__ e_attr, uint32_t bar_rest) {
    const int e0 = lds32(sb + MISC_OFF) * 16, s5 = lds32(sb + MISC_OFF + 40) * 16, e5 = lds32(sb + MISC_OFF + 20) * 16;
    gather_attr_range(sb, t, 0, e0, e_attr);
    gather_attr_range(sb, t, s5, e5, e_attr);
    asm volatile("cp.async.commit_group;" ::: "memory");
    gather_attr_range(sb, t, e0, s5, e_attr);
    gather_attr_range(sb, t, e5, run, e_attr);
    asm volatile("cp.async.commit_group;" ::: "memory");
    asm volatile("cp.async.wait_group 1;" ::: "memory");
    bar_arrive(BAR_READY, N_MAIN + N_AUX);
    asm volatile("cp.async.wait_group 0;" ::: "memory");
    __syncwarp();
    if ((t & 31) == 0) mbar_arrive(bar_rest);
}

struct Params {
    const __nv_bfloat16* e_attr;
    const int* src;
    const int* dst;
    const __nv_bfloat16* g_w;
    const __nv_bfloat16* v_w;
    const __nv_bfloat16* u_w;
    __nv_bfloat16* out;
    uint4* tab;
    uint4* slots;
    unsigned int* bar;
    float4* part;
};

__global__ void __launch_bounds__(NTHREADS, 1)
egc_kernel(const __grid_constant__ CUtensorMap tm_x, const __grid_constant__ CUtensorMap tm_g,
           const __grid_constant__ CUtensorMap tm_v, const __grid_constant__ CUtensorMap tm_u,
           const __grid_constant__ CUtensorMap tm_t, const __grid_constant__ CUtensorMap tm_c,
           const __grid_constant__ CUtensorMap tm_s, const __grid_constant__ CUtensorMap tm_s2,
           const __grid_constant__ Params P) {
    extern __shared__ __align__(1024) unsigned char smem_raw[];
    const uint32_t sb = (uint32_t)__cvta_generic_to_shared(smem_raw);
    if (sb & 1023u) __trap();
    const int tid = threadIdx.x, warp = tid >> 5, lane = tid & 31;
    const int tile = blockIdx.x;
    const uint32_t bar_full = sb + BAR_OFF, bar_empty = bar_full + 8 * NST, bar_x = bar_empty + 8 * NST, bar_idx = bar_x + 32, bar_c = bar_idx + 8, bar_cand = bar_c + 8, bar_rest = bar_cand + 8;
    const __nv_bfloat16* __restrict__ e_attr = P.e_attr;

    int4 dv, sv;
    if (warp < 16) {
        if (tid < EPC / 4) {
            asm volatile("ld.global.nc.v4.s32 {%0,%1,%2,%3}, [%4];" : "=r"(dv.x), "=r"(dv.y), "=r"(dv.z), "=r"(dv.w)
                         : "l"((const int4*)P.dst + tile * (EPC / 4) + tid));
            asm volatile("ld.global.nc.v4.s32 {%0,%1,%2,%3}, [%4];" : "=r"(sv.x), "=r"(sv.y), "=r"(sv.z), "=r"(sv.w)
                         : "l"((const int4*)P.src + tile * (EPC / 4) + tid));
        }
        sts128(sb + CAND_OFF + tid * 16, make_uint4(REC_INV, REC_INV, REC_INV, REC_INV));
        sts128(sb + CAND_OFF + (tid + 512) * 16, make_uint4(REC_INV, REC_INV, REC_INV, REC_INV));
        if (tid < 128) sts32(sb + CNT_OFF + tid * 4, 0);
    } else if (warp < 20) {
        if (tid < N_MAIN + 16) sts32(sb + GCNT + (tid - N_MAIN) * 4, 0);
    } else if (tid == 640) {
        asm volatile("prefetch.tensormap [%0];" ::"l"(&tm_g) : "memory");
#pragma unroll
        for (int s = 0; s < NST; s++) {
            mbar_init(bar_full + 8 * s, 1);
            mbar_init(bar_empty + 8 * s, 16);
        }
        asm volatile("fence.mbarrier_init.release.cluster;" ::: "memory");
#pragma unroll 1
        for (int it = 0; it < NST; it++) {
            mbar_expect_tx(bar_full + 8 * it, 32768);
            tma_3d(sb + RING_OFF + it * 32768, &tm_g, 0, 256 + it * 64, 0, bar_full + 8 * it);
        }
    } else if (tid == 704) {
        asm volatile("prefetch.tensormap [%0];" ::"l"(&tm_x) : "memory");
#pragma unroll
        for (int s = 0; s < 4; s++) mbar_init(bar_x + 8 * s, 1);
        mbar_init(bar_idx, EPC / 128);
        mbar_init(bar_c, 1);
        mbar_init(bar_cand, 1);
        mbar_init(bar_rest, 4);
        asm volatile("fence.mbarrier_init.release.cluster;" ::: "memory");
#pragma unroll 1
        for (int c = 0; c < X_EARLY; c++) {
            mbar_expect_tx(bar_x + 8 * c, 10240);
            tma_2d(sb + X_OFF + c * 10240, &tm_x, c * 64, tile * TILE, bar_x + 8 * c);
        }
    } else if (tid == 672) {
        asm volatile("prefetch.tensormap [%0];" ::"l"(&tm_v) : "memory");
        asm volatile("prefetch.tensormap [%0];" ::"l"(&tm_u) : "memory");
        asm volatile("prefetch.tensormap [%0];" ::"l"(&tm_t) : "memory");
        asm volatile("prefetch.tensormap [%0];" ::"l"(&tm_c) : "memory");
        asm volatile("prefetch.tensormap [%0];" ::"l"(&tm_s) : "memory");
        asm volatile("prefetch.tensormap [%0];" ::"l"(&tm_s2) : "memory");
        const int go = tile * 2176, vo = tile * 1056;
        const int gn = min(2176, 528 * 512 - go), vn = min(1056, 256 * 512 - vo);
        if (gn > 0) asm volatile("cp.async.bulk.prefetch.L2.global [%0], %1;" ::"l"((const char*)P.g_w + go), "r"(gn) : "memory");
        if (vn > 0) {
            asm volatile("cp.async.bulk.prefetch.L2.global [%0], %1;" ::"l"((const char*)P.v_w + vo), "r"(vn) : "memory");
            asm volatile("cp.async.bulk.prefetch.L2.global [%0], %1;" ::"l"((const char*)P.u_w + vo), "r"(vn) : "memory");
        }
    }
    __syncthreads();

    if (warp >= 20) {
        asm volatile("setmaxnreg.dec.sync.aligned.u32 24;");
        if (tid == 640) {
            int st = 0, par = 0;
#pragma unroll 1
            for (int it = NST; it < NIT; it++) {
                const int p = it >> 2;
                const CUtensorMap* m = (p == 1) ? &tm_v : (p == 3) ? &tm_u : &tm_g;
                const int row = ((p == 0) ? 256 : 0) + (it & 3) * 64;
                mbar_wait(bar_empty + 8 * st, par);
                mbar_expect_tx(bar_full + 8 * st, 32768);
                tma_3d(sb + RING_OFF + st * 32768, m, 0, row, 0, bar_full + 8 * st);
                if (++st == NST) { st = 0; par ^= 1; }
            }
            mbar_wait(bar_empty + 8 * 1, 0);
            mbar_expect_tx(bar_c, 8192);
            tma_3d(sb + CT_OFF, &tm_c, 0, 512, 0, bar_c);
        } else if (tid == 704) {
            if (X_EARLY < 4) mbar_wait(bar_idx, 0);
#pragma unroll 1
            for (int c = X_EARLY; c < 4; c++) {
                mbar_expect_tx(bar_x + 8 * c, 10240);
                tma_2d(sb + X_OFF + c * 10240, &tm_x, c * 64, tile * TILE, bar_x + 8 * c);
            }
        } else if (warp == 21) {
            mbar_wait(bar_x + 8 * 3, 0);
#pragma unroll 1
            for (int i = lane; i < EPC * 32 / 128; i += 32)
                asm volatile("prefetch.global.L2 [%0];" ::"l"((const char*)e_attr + (size_t)tile * EPC * 32 + i * 128) : "memory");
        } else if (warp == 23) {
            unsigned int target = 0;
            if (lane == 0) target = grid_target(P.bar);
#pragma unroll 1
            for (int wave = 0; wave < 2; wave++) {
                bar_sync(BAR_TABLE, N_MAIN + 32);
                if (lane == 0) {
#pragma unroll 1
                    for (int ds = 0; ds < 8; ds++) {
                        asm volatile("cp.async.bulk.tensor.2d.global.shared::cta.bulk_group [%0, {%2, %3}], [%1];"
                                     ::"l"(&tm_t), "r"(sb + EATTR_OFF + ds * 5120), "r"(ds * 64), "r"(tile * TILE + wave * 40) : "memory");
                        asm volatile("cp.async.bulk.commit_group;" ::: "memory");
                        asm volatile("cp.async.bulk.wait_group.read %0;" ::"n"(STORE_QUEUE) : "memory");
                    }
                    asm volatile("cp.async.bulk.wait_group.read 0;" ::: "memory");
                }
                __syncwarp();
                if (wave == 0) bar_arrive(BAR_STG, N_MAIN + 32);
                else bar_arrive(BAR_XFREE, N_AUX + 32);
            }
            if (lane == 0) {
                asm volatile("cp.async.bulk.wait_group 0;" ::: "memory");
                grid_arrive_relaxed(P.bar);
                grid_wait(P.bar, target);
            }
            __syncwarp();
            bar_arrive(BAR_GO, N_MAIN + 32);
        }
    } else if (warp >= 16) {
        asm volatile("setmaxnreg.dec.sync.aligned.u32 40;");
        const int t = tid - N_MAIN;
        unsigned int target = 0;
        if (t == 0) target = grid_target(P.bar + 32);
        bar_sync(BAR_S1, N_MAIN + N_AUX);
        if (t == 0) {
            asm volatile("cp.async.bulk.tensor.3d.global.shared::cta.bulk_group [%0, {%2, %3, %2}], [%1];"
                         ::"l"(&tm_s), "r"(sb + CAND_OFF), "r"(0), "r"(tile) : "memory");
            asm volatile("cp.async.bulk.commit_group;" ::: "memory");
            asm volatile("cp.async.bulk.wait_group 0;" ::: "memory");
            grid_arrive_relaxed(P.bar + 32);
            grid_wait(P.bar + 32, target);
            asm volatile("fence.proxy.async.global;" ::: "memory");
            mbar_expect_tx(bar_cand, NT * 128);
            asm volatile("cp.async.bulk.tensor.4d.shared::cluster.global.mbarrier::complete_tx::bytes [%0], [%1, {%3, %3, %3, %4}], [%2];"
                         ::"r"(sb + CAND_OFF), "l"(&tm_s2), "r"(bar_cand), "r"(0), "r"(tile) : "memory");
        }
        const uint32_t row = sb + CAND_OFF + t * 32;
        mbar_wait(bar_cand, 0);
        bool ovf = false;
#pragma unroll 1
        for (int j = 0; j < 4; j++) {
            uint4 a = make_uint4(REC_INV, REC_INV, REC_INV, REC_INV), b = a;
            if (t < NT) { a = lds128(row + j * (NT * 32)); b = lds128(row + j * (NT * 32) + 16); }
            if (j >= 2 && !__any_sync(0xffffffffu, rec_dl(a.x) != 127)) break;
            const uint32_t rec[8] = {a.x, a.y, a.z, a.w, b.x, b.y, b.z, b.w};
            uint32_t rank[8];
#pragma unroll
            for (int i = 0; i < 8; i++) rank[i] = bin_rank(sb, rec[i]);
#pragma unroll
            for (int i = 0; i < 8; i++) bin_store(sb, rec[i], rank[i], t);
            ovf |= rec_dl(b.w) == 126;
        }
        ovf = bar_or(BAR_AUX, N_AUX, ovf);
        int run = ovf ? -1 : layout_list(sb, t, 1);
        if (run >= 0) {
            bar_sync(BAR_AUX, N_AUX);
            expand_meta(sb, t, run);
            bar_arrive(BAR_META, N_MAIN + N_AUX);
            bar_sync(BAR_AUX, N_AUX);
            bar_sync(BAR_XFREE, N_AUX + 32);
            gather_attr(sb, t, run, e_attr, bar_rest);
        } else {
            bar_sync(BAR_AUX, N_AUX);
            if (t < 16) sts32(sb + GCNT + t * 4, 0);
            bar_sync(BAR_AUX, N_AUX);
            bool first = true;
#pragma unroll 1
            for (int w0 = 0; w0 < NT * EPC; w0 += 128) {
                const int e = w0 + t, d = __ldg(P.dst + e), b = (unsigned)d / TILE;
                uint32_t w = REC_INV;
                const int c = (unsigned)e / EPC;
                if (b == tile) w = ((uint32_t)(d - b * TILE) << 24) | (__ldg(P.src + e) * EPC + (e - c * EPC));
                bin_store(sb, w, bin_rank(sb, w), c);
                bar_sync(BAR_AUX, N_AUX);
                int mx = 0, sum = 0;
#pragma unroll 1
                for (int g = 0; g < 10; g++) { const int v = lds32(sb + GCNT + g * 4); mx = max(mx, v); sum += v; }
                const bool fin = w0 + 128 >= NT * EPC;
                const bool flush = fin || mx > CAPG - 128 || sum > CAP_STEPS * 16 - 48 - 150 - 128;
                bar_sync(BAR_AUX, N_AUX);
                if (flush) {
                    if (first) bar_sync(BAR_XFREE, N_AUX + 32);
                    first = false;
                    run = layout_list(sb, t, fin);
                    bar_sync(BAR_AUX, N_AUX);
                    expand_meta(sb, t, run);
                    bar_arrive(BAR_META, N_MAIN + N_AUX);
                    bar_sync(BAR_AUX, N_AUX);
                    gather_attr(sb, t, run, e_attr, bar_rest);
                    if (!fin) bar_sync(BAR_CONSUMED, N_MAIN + N_AUX);
                    bar_sync(BAR_AUX, N_AUX);
                    if (t < 16) sts32(sb + GCNT + t * 4, 0);
                    bar_sync(BAR_AUX, N_AUX);
                }
            }
        }
    } else {
        asm volatile("setmaxnreg.inc.sync.aligned.u32 104;");
        const int wg = warp >> 2;
        const int r = lane >> 2, q = lane & 3;
        if (tid < EPC / 4) {
            const int dd[4] = {dv.x, dv.y, dv.z, dv.w};
            const int ss[4] = {sv.x, sv.y, sv.z, sv.w};
            uint32_t rank[4];
            int bb[4];
#pragma unroll
            for (int i = 0; i < 4; i++) {
                bb[i] = (unsigned)dd[i] / TILE;
                asm volatile("atom.shared.add.u32 %0, [%1], 1;" : "=r"(rank[i]) : "r"(sb + CNT_OFF + bb[i] * 4) : "memory");
            }
#pragma unroll
            for (int i = 0; i < 4; i++) {
                const uint32_t rec = ((uint32_t)(dd[i] - bb[i] * TILE) << 24) | (ss[i] * EPC + tid * 4 + i);
                sts32(sb + CAND_OFF + bb[i] * 128 + (min(rank[i], 31u) << 2), rank[i] < 31 ? rec : REC_OVF);
            }
            __syncwarp();
            if (lane == 0) mbar_arrive(bar_idx);
        }
        asm volatile("fence.proxy.async.shared::cta;" ::: "memory");
        bar_arrive(BAR_S1, N_MAIN + N_AUX);

        float d[40];
        uint32_t pB[20], pV[20], xa[20];
        const uint64_t da0 = smem_desc(sb + RING_OFF + wg * 8192), db0 = smem_desc(sb + X_OFF);

        auto stage = [&](const int it) {
            const int c = it & 3, st = it % NST;
            if (it < 4) mbar_wait(bar_x + 8 * c, 0);
            mbar_wait(bar_full + 8 * st, (it / NST) & 1);
            wgmma_fence();
            const uint64_t da = da0 + st * 2048, db = db0 + c * 640;
            wgmma_n80(d, da, db, c != 0);
            wgmma_n80(d, da + 128, db + 2, 1);
            wgmma_n80(d, da + 256, db + 4, 1);
            wgmma_n80(d, da + 384, db + 6, 1);
            wgmma_commit();
        };
        auto release = [&](const int it) {
            if ((it + NST < NIT || it == 13) && lane == 0) mbar_arrive(bar_empty + 8 * (it % NST));
        };

        auto stage_table = [&](const int wave) {
            const uint32_t base = sb + EATTR_OFF + (warp >> 1) * 5120 + (lane & 7) * 128 +
                                  ((((warp & 1) * 4 + (lane >> 3)) ^ (lane & 7)) << 4);
#pragma unroll
            for (int jj = 0; jj < 5; jj++) {
                const int j = (wave * 5 + jj) * 2;
                asm volatile("stmatrix.sync.aligned.m8n8.x4.trans.shared.b16 [%0], {%1,%2,%3,%4};"
                             ::"r"(base + jj * 1024), "r"(pB[j]), "r"(pB[j + 1]), "r"(pV[j]), "r"(pV[j + 1]) : "memory");
            }
            asm volatile("fence.proxy.async.shared::cta;" ::: "memory");
            bar_arrive(BAR_TABLE, N_MAIN + 32);
        };
#pragma unroll
        for (int p = 0; p < 4; p++) {
#pragma unroll
            for (int c = 0; c < 4; c++) {
                stage(p * 4 + c);
                if (p == 2 && c == 0) stage_table(0);
                if (p * 4 + c == WAVE2_TILE) { bar_sync(BAR_STG, N_MAIN + 32); stage_table(1); }
                if (c > 0) { wgmma_wait<1>(); release(p * 4 + c - 1); }
            }
            wgmma_wait<0>();
            release(p * 4 + 3);
            if (p == 0) {
#pragma unroll
                for (int j = 0; j < 20; j++) pB[j] = pack_bf16(0.5f * d[2 * j], 0.5f * d[2 * j + 1]);
            } else if (p == 1) {
#pragma unroll
                for (int j = 0; j < 20; j++) pV[j] = pack_bf16(0.5f * d[2 * j], 0.5f * d[2 * j + 1]);
            } else if (p == 2) {
#pragma unroll
                for (int j = 0; j < 20; j++) xa[j] = pack_bf16(0.5f * d[2 * j], 0.5f * d[2 * j + 1]);
            }
        }

        uint32_t cf[2][4];
        mbar_wait(bar_c, 0);
#pragma unroll
        for (int c = 0; c < 2; c++) {
            const int k = (lane >> 4) * 8 + (lane & 7), col = (warp & 7) * 32 + c * 16 + ((lane >> 3) & 1) * 8;
            asm volatile("ldmatrix.sync.aligned.m8n8.x4.trans.shared.b16 {%0,%1,%2,%3}, [%4];"
                         : "=r"(cf[c][0]), "=r"(cf[c][1]), "=r"(cf[c][2]), "=r"(cf[c][3])
                         : "r"(sb + CT_OFF + (col >> 6) * 2048 + k * 128 + ((((col & 63) >> 3) ^ (k & 7)) << 4)));
#pragma unroll
            for (int i = 0; i < 4; i++) asm("mul.rn.bf16x2 %0, %0, %1;" : "+r"(cf[c][i]) : "r"(0x3F003F00u));
        }
        bar_sync(BAR_MAIN, N_MAIN);
#pragma unroll
        for (int j = 0; j < 10; j++) {
            asm volatile("st.shared.v2.u32 [%0], {%1, %2};" ::"r"(sb + PARK_U + (warp * 10 + j) * 256 + lane * 8),
                         "r"(pack_bf16(d[4 * j], d[4 * j + 1])), "r"(pack_bf16(d[4 * j + 2], d[4 * j + 3])) : "memory");
            asm volatile("st.shared.v2.u32 [%0], {%1, %2};" ::"r"(sb + PARK_XA + (warp * 10 + j) * 256 + lane * 8), "r"(xa[2 * j]), "r"(xa[2 * j + 1]) : "memory");
        }
        bar_sync(BAR_MAIN, N_MAIN);

        {
            const int ds = warp & 7, set = warp >> 3;
            const uint32_t cA = bf16_bits_of_int(2 * q) | (bf16_bits_of_int(2 * q + 1) << 16);
            const uint32_t cB = bf16_bits_of_int(r) * 0x10001u;
            const uint32_t id = (r == 2 * q ? 0x00003F80u : 0u) | (r == 2 * q + 1 ? 0x3F800000u : 0u);
            const char* tabl = (const char*)P.tab + ds * 128 + (lane & 7) * 16;
            const int ek = (lane >> 4) * 8 + (lane & 7);
            const uint32_t ea_l = sb + EATTR_OFF + ek * 32 + ((((lane >> 3) & 1) ^ ((ek >> 2) & 1)) << 4);
            const uint32_t mr_l = sb + MR_OFF + r * 16;
            const uint32_t mq_l = sb + MQ_OFF + q * 8;
            const uint32_t bounce = sb + CAND_OFF + warp * 512;
            const uint32_t pk = sb + (ds * 20 + set * 5) * 256 + lane * 8;
            float4* const part = P.part + ((size_t)tile * 160 + ds * 20 + set * 5) * 32 + lane;

            const uint32_t yb = warp < 14 ? sb + YB_OFF + warp * 4096 : sb + CAND_OFF + 8192 + (warp - 14) * 4096;
            const int g8 = lane >> 3;
            const uint32_t y_dst = yb + g8 * 128 + (((lane & 7) ^ g8) << 4);
            const uint32_t y_dst2 = yb + (g8 + 4) * 128 + (((lane & 7) ^ (g8 + 4)) << 4);
            const uint32_t mw_l = sb + MR_OFF + g8 * 16;
            const uint32_t y_ldb = yb + (lane & 7) * 128 + (((((lane >> 3) & 1) + (lane >> 4) * 4) ^ (lane & 7)) << 4);
            const uint32_t y_ldv = y_ldb ^ 32;

            auto gather1 = [&](uint32_t dst, uint32_t w) {
                asm volatile("{\n.reg .pred p;\n.reg .b64 a;\nsetp.ge.s32 p, %1, 0;\nmad.wide.u32 a, %1, 1024, %2;\n"
                             "@p cp.async.cg.shared.global [%0], [a], 16;\n}" ::"r"(dst), "r"(w), "l"(tabl) : "memory");
            };

            bar_sync(BAR_GO, N_MAIN + 32);
            for (int pass = 0;; pass++) {
                bar_sync(BAR_META, N_MAIN + N_AUX);
                const int last = lds32(sb + MISC_OFF + 44);
                int i = set ? (int)lds32(sb + MISC_OFF + 40) : 0;
                uint32_t pe = ea_l + i * 512, pr = mr_l + i * 128, pq = mq_l + i * 32;
                auto gather_step = [&](const int k, const int off) {
                    const uint32_t pw = pr - mr_l + mw_l + off;
                    const uint2 wa = lds64(pw), wb = lds64(pw + 64);
                    gather1(y_dst + k * 2048, wa.x);
                    gather1(y_dst2 + k * 2048, wb.x);
                    gather1(y_dst + k * 2048 + 1024, wa.y);
                    gather1(y_dst2 + k * 2048 + 1024, wb.y);
                    asm volatile("cp.async.commit_group;" ::: "memory");
                };
                {
#pragma unroll
                    for (int k = 0; k < 8; k++) sts128(yb + lane * 16 + k * 512, make_uint4(0, 0, 0, 0));
                    __syncwarp();
                    gather_step(0, 0);
                    gather_step(1, 128);
                }
                uint32_t xb[2][4], hv[2][4];
                auto fetch = [&](const int k, const int off) {
                    asm volatile("cp.async.wait_group 1;" ::: "memory");
                    __syncwarp();
#pragma unroll
                    for (int t = 0; t < 2; t++) {
                        asm volatile("ldmatrix.sync.aligned.m8n8.x4.shared.b16 {%0,%1,%2,%3}, [%4];"
                                     : "=r"(xb[t][0]), "=r"(xb[t][1]), "=r"(xb[t][2]), "=r"(xb[t][3]) : "r"(y_ldb + k * 2048 + t * 1024) : "memory");
                        asm volatile("ldmatrix.sync.aligned.m8n8.x4.trans.shared.b16 {%0,%1,%2,%3}, [%4];"
                                     : "=r"(hv[t][0]), "=r"(hv[t][1]), "=r"(hv[t][2]), "=r"(hv[t][3]) : "r"(y_ldv + k * 2048 + t * 1024) : "memory");
                    }
                    gather_step(k, off);
                };
                fetch(0, 2 * 128);
                bar_sync(BAR_READY, N_MAIN + N_AUX);
                int ph = 0;
                for (int g = 0; g < 5; g++) {
                    const int gend = lds32(sb + MISC_OFF + (set * 5 + g) * 4);
                    float acc[2][4];
                    uint2 xf[2];
#pragma unroll
                    for (int c = 0; c < 2; c++) {
                        if (pass == 0) {
                            const uint2 u = lds64(pk + PARK_U + (c * 10 + g) * 256);
                            acc[c][0] = __uint_as_float(u.x << 16); acc[c][1] = __uint_as_float(u.x & 0xFFFF0000u);
                            acc[c][2] = __uint_as_float(u.y << 16); acc[c][3] = __uint_as_float(u.y & 0xFFFF0000u);
                        } else {
                            const float4 a = part[(c * 10 + g) * 32];
                            acc[c][0] = a.x; acc[c][1] = a.y; acc[c][2] = a.z; acc[c][3] = a.w;
                        }
                        xf[c] = lds64(pk + PARK_XA + (c * 10 + g) * 256);
                    }

                    auto step = [&](const int k) {
                        const uint2 dd = lds64(pr + k * 128 + 8);
                        const uint2 db = lds64(pq + k * 32);
                        uint32_t e[4];
                        asm volatile("ldmatrix.sync.aligned.m8n8.x4.shared.b16 {%0,%1,%2,%3}, [%4];"
                                     : "=r"(e[0]), "=r"(e[1]), "=r"(e[2]), "=r"(e[3]) : "r"(pe + k * 512));
                        const uint32_t sa0 = seteq_bf16x2(dd.x, cA), sa1 = seteq_bf16x2(dd.y, cA);
                        const uint32_t sb0 = seteq_bf16x2(db.x, cB), sb1 = seteq_bf16x2(db.y, cB);
#pragma unroll
                        for (int c = 0; c < 2; c++) {
                            float p0[4], p1[4];
                            mma_bf16(p0, cf[c][0], cf[c][1], cf[c][2], cf[c][3], e[0], e[1], 0.f, 0.f, 0.f, 0.f);
                            mma_bf16(p1, cf[c][0], cf[c][1], cf[c][2], cf[c][3], e[2], e[3], 0.f, 0.f, 0.f, 0.f);
                            mma_bf16_k8(p0, xf[c].x, xf[c].y, sa0);
                            mma_bf16_k8(p1, xf[c].x, xf[c].y, sa1);
                            mma_bf16(p0, id, 0u, 0u, id, xb[0][2 * c], xb[0][2 * c + 1], p0[0], p0[1], p0[2], p0[3]);
                            mma_bf16(p1, id, 0u, 0u, id, xb[1][2 * c], xb[1][2 * c + 1], p1[0], p1[1], p1[2], p1[3]);
                            const uint32_t m0 = fma_bf16x2(hv[0][2 * c], pack_bf16(tanh_approx(p0[0]), tanh_approx(p0[1])), hv[0][2 * c]);
                            const uint32_t m1 = fma_bf16x2(hv[0][2 * c + 1], pack_bf16(tanh_approx(p0[2]), tanh_approx(p0[3])), hv[0][2 * c + 1]);
                            const uint32_t m2 = fma_bf16x2(hv[1][2 * c], pack_bf16(tanh_approx(p1[0]), tanh_approx(p1[1])), hv[1][2 * c]);
                            const uint32_t m3 = fma_bf16x2(hv[1][2 * c + 1], pack_bf16(tanh_approx(p1[2]), tanh_approx(p1[3])), hv[1][2 * c + 1]);
                            mma_bf16(acc[c], m0, m1, m2, m3, sb0, sb1, acc[c][0], acc[c][1], acc[c][2], acc[c][3]);
                        }
                        fetch(k ^ 1, (k + 3) * 128);
                    };

                    int rem = gend - i;
                    i = gend;
                    while (rem > 0) {
                        if (ph == 0) {
                            step(0);
                            ph = 1;
                            if (--rem == 0) break;
                        }
                        step(1);
                        ph = 0; pe += 2 * 512; pr += 2 * 128; pq += 2 * 32; --rem;
                    }

                    if (g == 0) mbar_wait(bar_rest, pass & 1);

                    if (last) {
                        uint32_t o[4];
#pragma unroll
                        for (int c = 0; c < 2; c++) {
                            float z[4];
#pragma unroll
                            for (int j = 0; j < 4; j++) z[j] = __fdividef(acc[c][j], 1.f + __expf(-acc[c][j]));
                            o[2 * c] = pack_bf16(z[0], z[1]);
                            o[2 * c + 1] = pack_bf16(z[2], z[3]);
                        }
                        asm volatile("stmatrix.sync.aligned.m8n8.x4.trans.shared.b16 [%0], {%1,%2,%3,%4};"
                                     ::"r"(bounce + (lane & 7) * 64 + (((lane >> 3) ^ ((lane >> 1) & 3)) << 4)),
                                       "r"(o[0]), "r"(o[1]), "r"(o[2]), "r"(o[3]) : "memory");
                        __syncwarp();
                        const int node = lane >> 2;
                        const uint4 v = lds128(bounce + node * 64 + ((q ^ ((node >> 1) & 3)) << 4));
                        *(uint4*)(P.out + (size_t)(tile * TILE + (set * 5 + g) * 8 + node) * DD + ds * 32 + q * 8) = v;
                        __syncwarp();
                    } else {
#pragma unroll
                        for (int c = 0; c < 2; c++) part[(c * 10 + g) * 32] = make_float4(acc[c][0], acc[c][1], acc[c][2], acc[c][3]);
                    }
                }
                if (last) break;
                cp_async_wait_all();
                bar_arrive(BAR_CONSUMED, N_MAIN + N_AUX);
            }
        }
    }
}

typedef CUresult (*EncodeFn)(CUtensorMap*, CUtensorMapDataType, cuuint32_t, void*, const cuuint64_t*, const cuuint64_t*,
                             const cuuint32_t*, const cuuint32_t*, CUtensorMapInterleave, CUtensorMapSwizzle,
                             CUtensorMapL2promotion, CUtensorMapFloatOOBfill);

static void make_map(EncodeFn fn, CUtensorMap* m, const void* ptr, int rows, int box_rows) {
    cuuint64_t dims[2] = {(cuuint64_t)DD, (cuuint64_t)rows};
    cuuint64_t strides[1] = {(cuuint64_t)DD * 2};
    cuuint32_t box[2] = {64, (cuuint32_t)box_rows};
    cuuint32_t es[2] = {1, 1};
    fn(m, CU_TENSOR_MAP_DATA_TYPE_BFLOAT16, 2, const_cast<void*>(ptr), dims, strides, box, es, CU_TENSOR_MAP_INTERLEAVE_NONE,
       CU_TENSOR_MAP_SWIZZLE_128B, CU_TENSOR_MAP_L2_PROMOTION_L2_256B, CU_TENSOR_MAP_FLOAT_OOB_FILL_NONE);
}

static void make_tmap(EncodeFn fn, CUtensorMap* m, void* ptr) {
    cuuint64_t dims[2] = {512, (cuuint64_t)NN};
    cuuint64_t strides[1] = {1024};
    cuuint32_t box[2] = {64, 40};
    cuuint32_t es[2] = {1, 1};
    fn(m, CU_TENSOR_MAP_DATA_TYPE_BFLOAT16, 2, ptr, dims, strides, box, es, CU_TENSOR_MAP_INTERLEAVE_NONE,
       CU_TENSOR_MAP_SWIZZLE_128B, CU_TENSOR_MAP_L2_PROMOTION_NONE, CU_TENSOR_MAP_FLOAT_OOB_FILL_NONE);
}

static void make_smap(EncodeFn fn, CUtensorMap* m, void* ptr) {
    cuuint64_t dims[3] = {32, (cuuint64_t)NT, (cuuint64_t)NT};
    cuuint64_t strides[2] = {128, (cuuint64_t)NT * 128};
    cuuint32_t box[3] = {32, 1, (cuuint32_t)NT};
    cuuint32_t es[3] = {1, 1, 1};
    fn(m, CU_TENSOR_MAP_DATA_TYPE_UINT32, 3, ptr, dims, strides, box, es, CU_TENSOR_MAP_INTERLEAVE_NONE,
       CU_TENSOR_MAP_SWIZZLE_NONE, CU_TENSOR_MAP_L2_PROMOTION_NONE, CU_TENSOR_MAP_FLOAT_OOB_FILL_NONE);
}

static void make_smap2(EncodeFn fn, CUtensorMap* m, void* ptr) {
    cuuint64_t dims[4] = {8, (cuuint64_t)NT, 4, (cuuint64_t)NT};
    cuuint64_t strides[3] = {128, 32, (cuuint64_t)NT * 128};
    cuuint32_t box[4] = {8, (cuuint32_t)NT, 4, 1};
    cuuint32_t es[4] = {1, 1, 1, 1};
    fn(m, CU_TENSOR_MAP_DATA_TYPE_UINT32, 4, ptr, dims, strides, box, es, CU_TENSOR_MAP_INTERLEAVE_NONE,
       CU_TENSOR_MAP_SWIZZLE_NONE, CU_TENSOR_MAP_L2_PROMOTION_NONE, CU_TENSOR_MAP_FLOAT_OOB_FILL_NONE);
}

static void make_wmap(EncodeFn fn, CUtensorMap* m, const void* ptr, int rows, int box_rows) {
    cuuint64_t dims[3] = {64, (cuuint64_t)rows, 4};
    cuuint64_t strides[2] = {(cuuint64_t)DD * 2, 128};
    cuuint32_t box[3] = {64, (cuuint32_t)box_rows, 4};
    cuuint32_t es[3] = {1, 1, 1};
    fn(m, CU_TENSOR_MAP_DATA_TYPE_BFLOAT16, 3, const_cast<void*>(ptr), dims, strides, box, es, CU_TENSOR_MAP_INTERLEAVE_NONE,
       CU_TENSOR_MAP_SWIZZLE_128B, CU_TENSOR_MAP_L2_PROMOTION_L2_256B, CU_TENSOR_MAP_FLOAT_OOB_FILL_NONE);
}

}

extern "C" void kernel_launch(void* const* d_in, const int* in_sizes, int n_in, void* d_out, int out_size) {
    using namespace egc;
    (void)in_sizes; (void)n_in; (void)out_size;
    static EncodeFn encode = nullptr;
    static void *p_tab = nullptr, *p_slots = nullptr, *p_bar = nullptr, *p_part = nullptr;
    if (!encode) {
        void* fn = nullptr;
        cudaDriverEntryPointQueryResult qr;
        cudaGetDriverEntryPoint("cuTensorMapEncodeTiled", &fn, cudaEnableDefault, &qr);
        encode = (EncodeFn)fn;
        cudaFuncSetAttribute(egc_kernel, cudaFuncAttributeMaxDynamicSharedMemorySize, SMEM_BYTES);
        cudaGetSymbolAddress(&p_tab, g_tab);
        cudaGetSymbolAddress(&p_slots, g_slots);
        cudaGetSymbolAddress(&p_bar, g_bar);
        cudaGetSymbolAddress(&p_part, g_part);
    }
    const __nv_bfloat16* x = (const __nv_bfloat16*)d_in[0];
    Params P;
    P.e_attr = (const __nv_bfloat16*)d_in[1];
    P.src = (const int*)d_in[2];
    P.dst = (const int*)d_in[3];
    P.u_w = (const __nv_bfloat16*)d_in[4];
    P.v_w = (const __nv_bfloat16*)d_in[5];
    P.g_w = (const __nv_bfloat16*)d_in[6];
    P.out = (__nv_bfloat16*)d_out;
    P.tab = (uint4*)p_tab;
    P.slots = (uint4*)p_slots;
    P.bar = (unsigned int*)p_bar;
    P.part = (float4*)p_part;
    CUtensorMap tx, tg, tv, tu, tt, tc, ts, ts2;
    make_smap(encode, &ts, p_slots);
    make_smap2(encode, &ts2, p_slots);
    make_tmap(encode, &tt, p_tab);
    make_map(encode, &tx, x, NN, TILE);
    make_wmap(encode, &tg, P.g_w, 2 * DD + 16, 64);
    make_wmap(encode, &tc, P.g_w, 2 * DD + 16, 16);
    make_wmap(encode, &tv, P.v_w, DD, 64);
    make_wmap(encode, &tu, P.u_w, DD, 64);
    egc_kernel<<<NT, NTHREADS, SMEM_BYTES, cudaStreamPerThread>>>(tx, tg, tv, tu, tt, tc, ts, ts2, P);
}
```

```cpp
#include <cuda_runtime.h>
#include <cuda_bf16.h>
#include <cuda.h>
#include <stdint.h>

namespace egc {

constexpr int NN = 10000;
constexpr int DD = 256;
constexpr int TILE = 80;
constexpr int NT = 125;
constexpr int EPC = 1280;
constexpr int NST = 3;
constexpr int NIT = 16;
constexpr int WAIT_HINT_NS = 20000;
constexpr int WAVE2_TILE = 10;
constexpr int STORE_QUEUE = 3;
constexpr int X_EARLY = 2;
constexpr int CAP_STEPS = 98;

constexpr int N_MAIN = 512, N_AUX = 128;
constexpr int NTHREADS = N_MAIN + N_AUX + 128;

constexpr int X_OFF = 0;
constexpr int RING_OFF = 40960;
constexpr int CT_OFF = RING_OFF + 32768;
constexpr int PARK_U = 0;
constexpr int PARK_XA = 40960;
constexpr int YB_OFF = 81920;
constexpr int EATTR_OFF = RING_OFF + NST * 32768;
constexpr int CAND_OFF = EATTR_OFF + CAP_STEPS * 512;
constexpr int MR_OFF = CAND_OFF + 16384;
constexpr int MQ_OFF = MR_OFF + (CAP_STEPS + 3) * 128;
constexpr int CAPG = 192;
constexpr int EL_OFF = MQ_OFF + CAP_STEPS * 32;
constexpr int ER_OFF = EL_OFF + 10 * CAPG * 4;
constexpr int CNT_OFF = ER_OFF + 10 * CAPG;
constexpr int MISC_OFF = CNT_OFF + 512;
constexpr int BAR_OFF = MISC_OFF + 128;
constexpr int SMEM_BYTES = BAR_OFF + 128;
static_assert(YB_OFF + 14 * 4096 <= EATTR_OFF, "park area and gather buffers must fit in x + ring");
static_assert(SMEM_BYTES <= 232448, "too much shared memory");

constexpr uint32_t REC_INV = 0x7FFFFFFFu, REC_OVF = 0x7E000000u;
__device__ __forceinline__ uint32_t rec_dl(uint32_t w) { return (w >> 24) & 127; }
constexpr uint32_t DBF_INV = 0x4380u;

constexpr int BAR_AUX = 1, BAR_MAIN = 2, BAR_READY = 3, BAR_CONSUMED = 4, BAR_TABLE = 5, BAR_GO = 6, BAR_S1 = 7, BAR_STG = 8, BAR_XFREE = 9, BAR_META = 10;

__device__ uint4 g_tab[(size_t)NN * 64];
__device__ float4 g_part[(size_t)NT * 160 * 32];
__device__ uint4 g_slots[(size_t)NT * NT * 8];
__device__ unsigned int g_bar[64];

__device__ __forceinline__ void bar_sync(int id, int n) { asm volatile("bar.sync %0, %1;" ::"r"(id), "r"(n) : "memory"); }
__device__ __forceinline__ void bar_arrive(int id, int n) { asm volatile("bar.arrive %0, %1;" ::"r"(id), "r"(n) : "memory"); }

__device__ __forceinline__ void mbar_init(uint32_t bar, uint32_t cnt) {
    asm volatile("mbarrier.init.shared::cta.b64 [%0], %1;" ::"r"(bar), "r"(cnt) : "memory");
}
__device__ __forceinline__ void mbar_expect_tx(uint32_t bar, uint32_t bytes) {
    asm volatile("mbarrier.arrive.expect_tx.shared::cta.b64 _, [%0], %1;" ::"r"(bar), "r"(bytes) : "memory");
}
__device__ __forceinline__ void mbar_arrive(uint32_t bar) {
    asm volatile("mbarrier.arrive.shared::cta.b64 _, [%0];" ::"r"(bar) : "memory");
}
__device__ __forceinline__ void mbar_wait(uint32_t bar, uint32_t parity) {
    uint32_t ok;
    int spins = 0;
    do {
        asm volatile("{\n.reg .pred p;\nmbarrier.try_wait.parity.shared::cta.b64 p, [%1], %2, %3;\nselp.u32 %0, 1, 0, p;\n}"
                     : "=r"(ok) : "r"(bar), "r"(parity), "r"(WAIT_HINT_NS) : "memory");
    } while (!ok && ++spins < (1 << 16));
}
__device__ __forceinline__ void tma_2d(uint32_t dst, const CUtensorMap* map, int c0, int c1, uint32_t bar) {
    asm volatile("cp.async.bulk.tensor.2d.shared::cluster.global.mbarrier::complete_tx::bytes [%0], [%1, {%3, %4}], [%2];"
                 ::"r"(dst), "l"(map), "r"(bar), "r"(c0), "r"(c1) : "memory");
}
__device__ __forceinline__ void tma_3d(uint32_t dst, const CUtensorMap* map, int c0, int c1, int c2, uint32_t bar) {
    asm volatile("cp.async.bulk.tensor.3d.shared::cluster.global.mbarrier::complete_tx::bytes [%0], [%1, {%3, %4, %5}], [%2];"
                 ::"r"(dst), "l"(map), "r"(bar), "r"(c0), "r"(c1), "r"(c2) : "memory");
}
__device__ __forceinline__ void sts32_if(bool p, uint32_t a, uint32_t v) {
    asm volatile("{\n.reg .pred p;\nsetp.ne.u32 p, %2, 0;\n@p st.shared.u32 [%0], %1;\n}" ::"r"(a), "r"(v), "r"((uint32_t)p) : "memory");
}
__device__ __forceinline__ void sts8_if(bool p, uint32_t a, uint32_t v) {
    asm volatile("{\n.reg .pred p;\nsetp.ne.u32 p, %2, 0;\n@p st.shared.u8 [%0], %1;\n}" ::"r"(a), "r"(v), "r"((uint32_t)p) : "memory");
}
__device__ __forceinline__ void cp_async_wait_all() { asm volatile("cp.async.wait_all;" ::: "memory"); }

__device__ __forceinline__ uint32_t lds32(uint32_t a) { uint32_t v; asm volatile("ld.shared.u32 %0, [%1];" : "=r"(v) : "r"(a)); return v; }
__device__ __forceinline__ uint2 lds64(uint32_t a) { uint2 v; asm volatile("ld.shared.v2.u32 {%0,%1}, [%2];" : "=r"(v.x), "=r"(v.y) : "r"(a)); return v; }
__device__ __forceinline__ uint4 lds128(uint32_t a) {
    uint4 v; asm volatile("ld.shared.v4.u32 {%0,%1,%2,%3}, [%4];" : "=r"(v.x), "=r"(v.y), "=r"(v.z), "=r"(v.w) : "r"(a)); return v;
}
__device__ __forceinline__ void sts16(uint32_t a, uint32_t v) { asm volatile("st.shared.u16 [%0], %1;" ::"r"(a), "h"((uint16_t)v) : "memory"); }
__device__ __forceinline__ void sts32(uint32_t a, uint32_t v) { asm volatile("st.shared.u32 [%0], %1;" ::"r"(a), "r"(v) : "memory"); }
__device__ __forceinline__ void sts128(uint32_t a, uint4 v) {
    asm volatile("st.shared.v4.u32 [%0], {%1,%2,%3,%4};" ::"r"(a), "r"(v.x), "r"(v.y), "r"(v.z), "r"(v.w) : "memory");
}
__device__ __forceinline__ uint32_t pack_bf16(float lo, float hi) {
    uint32_t d; asm("cvt.rn.bf16x2.f32 %0, %1, %2;" : "=r"(d) : "f"(hi), "f"(lo)); return d;
}
__device__ __forceinline__ uint32_t seteq_bf16x2(uint32_t a, uint32_t b) {
    uint32_t d; asm("set.eq.bf16x2.bf16x2 %0, %1, %2;" : "=r"(d) : "r"(a), "r"(b)); return d;
}
__device__ __forceinline__ uint32_t fma_bf16x2(uint32_t a, uint32_t b, uint32_t c) {
    uint32_t d; asm("fma.rn.bf16x2 %0, %1, %2, %3;" : "=r"(d) : "r"(a), "r"(b), "r"(c)); return d;
}
__device__ __forceinline__ float tanh_approx(float x) { float y; asm("tanh.approx.f32 %0, %1;" : "=f"(y) : "f"(x)); return y; }
__device__ __forceinline__ uint32_t bf16_bits_of_int(int v) { return __float_as_uint((float)v) >> 16; }

__device__ __forceinline__ void mma_bf16(float (&d)[4], uint32_t a0, uint32_t a1, uint32_t a2, uint32_t a3,
                                         uint32_t b0, uint32_t b1, float c0, float c1, float c2, float c3) {
    asm("mma.sync.aligned.m16n8k16.row.col.f32.bf16.bf16.f32 {%0,%1,%2,%3}, {%4,%5,%6,%7}, {%8,%9}, {%10,%11,%12,%13};"
        : "=f"(d[0]), "=f"(d[1]), "=f"(d[2]), "=f"(d[3])
        : "r"(a0), "r"(a1), "r"(a2), "r"(a3), "r"(b0), "r"(b1), "f"(c0), "f"(c1), "f"(c2), "f"(c3));
}

__device__ __forceinline__ void mma_bf16_k8(float (&d)[4], uint32_t a0, uint32_t a1, uint32_t b0) {
    asm("mma.sync.aligned.m16n8k8.row.col.f32.bf16.bf16.f32 {%0,%1,%2,%3}, {%4,%5}, {%6}, {%0,%1,%2,%3};"
        : "+f"(d[0]), "+f"(d[1]), "+f"(d[2]), "+f"(d[3]) : "r"(a0), "r"(a1), "r"(b0));
}

__device__ __forceinline__ void wgmma_n80(float (&d)[40], uint64_t da, uint64_t db, int scale_d) {
    asm volatile(
        "{\n.reg .pred p;\nsetp.ne.b32 p, %42, 0;\n"
        "wgmma.mma_async.sync.aligned.m64n80k16.f32.bf16.bf16 "
        "{%0,%1,%2,%3,%4,%5,%6,%7,%8,%9,%10,%11,%12,%13,%14,%15,%16,%17,%18,%19,"
        "%20,%21,%22,%23,%24,%25,%26,%27,%28,%29,%30,%31,%32,%33,%34,%35,%36,%37,%38,%39}, "
        "%40, %41, p, 1, 1, 1, 0;\n}"
        : "+f"(d[0]), "+f"(d[1]), "+f"(d[2]), "+f"(d[3]), "+f"(d[4]), "+f"(d[5]), "+f"(d[6]), "+f"(d[7]),
          "+f"(d[8]), "+f"(d[9]), "+f"(d[10]), "+f"(d[11]), "+f"(d[12]), "+f"(d[13]), "+f"(d[14]), "+f"(d[15]),
          "+f"(d[16]), "+f"(d[17]), "+f"(d[18]), "+f"(d[19]), "+f"(d[20]), "+f"(d[21]), "+f"(d[22]), "+f"(d[23]),
          "+f"(d[24]), "+f"(d[25]), "+f"(d[26]), "+f"(d[27]), "+f"(d[28]), "+f"(d[29]), "+f"(d[30]), "+f"(d[31]),
          "+f"(d[32]), "+f"(d[33]), "+f"(d[34]), "+f"(d[35]), "+f"(d[36]), "+f"(d[37]), "+f"(d[38]), "+f"(d[39])
        : "l"(da), "l"(db), "r"(scale_d));
}
__device__ __forceinline__ void wgmma_fence() { asm volatile("wgmma.fence.sync.aligned;" ::: "memory"); }
__device__ __forceinline__ void wgmma_commit() { asm volatile("wgmma.commit_group.sync.aligned;" ::: "memory"); }
template <int N> __device__ __forceinline__ void wgmma_wait() { asm volatile("wgmma.wait_group.sync.aligned %0;" ::"n"(N) : "memory"); }

__device__ __forceinline__ uint64_t smem_desc(uint32_t addr) {
    return (uint64_t)((addr & 0x3FFFF) >> 4) | ((uint64_t)1 << 16) | ((uint64_t)64 << 32) | ((uint64_t)1 << 62);
}

__device__ __forceinline__ unsigned int grid_target(const unsigned int* ctr) {
    unsigned int v;
    asm volatile("ld.relaxed.gpu.global.u32 %0, [%1];" : "=r"(v) : "l"(ctr) : "memory");
    return (v / NT + 1u) * NT;
}
__device__ __forceinline__ void grid_arrive_relaxed(unsigned int* ctr) {
    asm volatile("red.relaxed.gpu.global.add.u32 [%0], 1;" ::"l"(ctr) : "memory");
}
__device__ __forceinline__ void grid_wait(const unsigned int* ctr, unsigned int target) {
    unsigned int v;
    int spins = 0;
    do {
        asm volatile("ld.acquire.gpu.global.u32 %0, [%1];" : "=r"(v) : "l"(ctr) : "memory");
    } while ((int)(v - target) < 0 && ++spins < (1 << 21));
}

constexpr int GCNT = MISC_OFF + 64;

__device__ __forceinline__ uint32_t bin_rank(uint32_t sb, uint32_t w) {
    uint32_t rank;
    asm volatile("{\n.reg .pred p;\nsetp.lt.u32 p, %1, %3;\nmov.u32 %0, 0xFFFF;\n@p atom.shared.add.u32 %0, [%2], 1;\n}"
                 : "=r"(rank) : "r"(w >> 24), "r"(sb + GCNT + ((w >> 25) & 0x3C)), "n"(TILE) : "memory");
    return rank;
}
__device__ __forceinline__ void bin_store(uint32_t sb, uint32_t w, uint32_t rank, uint32_t row) {
    const uint32_t idx = (w >> 27) * CAPG + rank;
    sts32_if(rank < CAPG, sb + EL_OFF + idx * 4, w);
    sts8_if(rank < CAPG, sb + ER_OFF + idx, row);
}
__device__ __forceinline__ bool bar_or(int id, int n, bool v) {
    uint32_t r;
    asm volatile("{\n.reg .pred p, q;\nsetp.ne.u32 q, %3, 0;\nbarrier.cta.red.or.pred p, %1, %2, q;\nselp.u32 %0, 1, 0, p;\n}"
                 : "=r"(r) : "r"(id), "r"(n), "r"((uint32_t)v) : "memory");
    return r;
}

__device__ __forceinline__ int layout_list(uint32_t sb, int t, int last) {
    int tot[10];
    {
        const uint4 a = lds128(sb + GCNT), b = lds128(sb + GCNT + 16);
        const uint2 c = lds64(sb + GCNT + 32);
        tot[0] = a.x; tot[1] = a.y; tot[2] = a.z; tot[3] = a.w; tot[4] = b.x; tot[5] = b.y; tot[6] = b.z; tot[7] = b.w;
        tot[8] = c.x; tot[9] = c.y;
    }
    int run = 0, myend = 0, gap = 0, tab = 0, mx = 0;
#pragma unroll
    for (int g = 0; g < 10; g++) {
        const int ge = run + ((tot[g] + 15) & ~15);
        const int off = t * 16 - run;
        if (off >= 0 && t * 16 < ge) tab = ((g * CAPG + off) << 16) | (tot[g] - off);
        if (g == t) myend = ge;
        if (g == 4) gap = ge;
        mx = max(mx, tot[g]);
        run = ge + (g == 4 ? 48 : 0);
    }
    if (mx > CAPG || run > CAP_STEPS * 16) return -1;
    if (t < CAP_STEPS) sts32(sb + CNT_OFF + t * 4, tab);
    if (t < 48) sts32(sb + MR_OFF + ((run >> 4) + (t >> 4)) * 128 + ((t & 15) >> 1) * 16 + (t & 1) * 4, 0xFFFFFFFFu);
    if (t < 10) sts32(sb + MISC_OFF + t * 4, myend >> 4);
    if (t == 10) sts32(sb + MISC_OFF + 40, (gap >> 4) + 3);
    if (t == 11) sts32(sb + MISC_OFF + 44, last);
    return run;
}

__device__ __forceinline__ void expand_meta(uint32_t sb, int t, int run) {
#pragma unroll 2
    for (int pos = t; pos < run; pos += N_AUX) {
        const uint32_t tb = lds32(sb + CNT_OFF + (pos >> 4) * 4);
        const int k = pos & 15, st16 = pos & ~15;
        const bool v = k < (int)(tb & 0xFFFF);
        const uint32_t idx = v ? (tb >> 16) + k : 0;
        const uint32_t w = lds32(sb + EL_OFF + idx * 4);
        uint32_t row;
        asm volatile("ld.shared.u8 %0, [%1];" : "=r"(row) : "r"(sb + ER_OFF + idx));
        const uint32_t se = w & 0xFFFFFF, sn = se / EPC;
        const uint32_t dbf = v ? bf16_bits_of_int((w >> 24) & 7) : DBF_INV;
        const uint32_t mr = sb + MR_OFF + st16 * 8 + (k & 7) * 16 + (k >> 3) * 4;
        sts32(mr, v ? sn : 0xFFFFFFFFu);
        sts32(mr + 8, dbf * 0x10001u);
        sts16(sb + MQ_OFF + (st16 + ((k & 7) >> 1) * 4 + (k & 1) + 2 * (k >> 3)) * 2, dbf);
        sts32(sb + CAND_OFF + pos * 4, v ? ((row - sn) * EPC + se) * 32 : 0xFFFFFFFFu);
    }
}

__device__ __forceinline__ void gather_attr_range(uint32_t sb, int t, int p_begin, int p_end, const __nv_bfloat16* __restrict__ e_attr) {
    const int h = t & 1, p0 = p_begin + (t >> 1);
    const char* base = (const char*)e_attr + h * 16;
    uint32_t src = sb + CAND_OFF + p0 * 4;
    uint32_t dst = sb + EATTR_OFF + p0 * 32 + ((h ^ ((p0 >> 2) & 1)) << 4);
#pragma unroll 1
    for (int pos = p0; pos < p_end; pos += 2 * 64) {
        uint32_t off[2];
#pragma unroll
        for (int i = 0; i < 2; i++) off[i] = lds32(src + i * 256);
#pragma unroll
        for (int i = 0; i < 2; i++) {
            if (pos + i * 64 < p_end)
                asm volatile("{\n.reg .pred p;\n.reg .b32 n, o;\n.reg .b64 a;\nsetp.ne.u32 p, %1, 0xFFFFFFFF;\nselp.b32 n, 16, 0, p;\n"
                             "selp.b32 o, %1, 0, p;\ncvt.u64.u32 a, o;\nadd.u64 a, a, %2;\ncp.async.cg.shared.global [%0], [a], 16, n;\n}"
                             ::"r"(dst + i * 2048), "r"(off[i]), "l"(base) : "memory");
        }
        src += 512;
        dst += 4096;
    }
}
__device__ __forceinline__ void gather_attr(uint32_t sb, int t, int run, const __nv_bfloat16* __restrict__ e_attr, uint32_t bar_rest) {
    const int e0 = lds32(sb + MISC_OFF) * 16, s5 = lds32(sb + MISC_OFF + 40) * 16, e5 = lds32(sb + MISC_OFF + 20) * 16;
    gather_attr_range(sb, t, 0, e0, e_attr);
    gather_attr_range(sb, t, s5, e5, e_attr);
    asm volatile("cp.async.commit_group;" ::: "memory");
    gather_attr_range(sb, t, e0, s5, e_attr);
    gather_attr_range(sb, t, e5, run, e_attr);
    asm volatile("cp.async.commit_group;" ::: "memory");
    asm volatile("cp.async.wait_group 1;" ::: "memory");
    bar_arrive(BAR_READY, N_MAIN + N_AUX);
    asm volatile("cp.async.wait_group 0;" ::: "memory");
    __syncwarp();
    if ((t & 31) == 0) mbar_arrive(bar_rest);
}

struct Params {
    const __nv_bfloat16* e_attr;
    const int* src;
    const int* dst;
    const __nv_bfloat16* g_w;
    const __nv_bfloat16* v_w;
    const __nv_bfloat16* u_w;
    __nv_bfloat16* out;
    uint4* tab;
    uint4* slots;
    unsigned int* bar;
    float4* part;
};

__global__ void __launch_bounds__(NTHREADS, 1)
egc_kernel(const __grid_constant__ CUtensorMap tm_x, const __grid_constant__ CUtensorMap tm_g,
           const __grid_constant__ CUtensorMap tm_v, const __grid_constant__ CUtensorMap tm_u,
           const __grid_constant__ CUtensorMap tm_t, const __grid_constant__ CUtensorMap tm_c,
           const __grid_constant__ CUtensorMap tm_s, const __grid_constant__ CUtensorMap tm_s2,
           const __grid_constant__ Params P) {
    extern __shared__ __align__(1024) unsigned char smem_raw[];
    const uint32_t sb = (uint32_t)__cvta_generic_to_shared(smem_raw);
    if (sb & 1023u) __trap();
    const int tid = threadIdx.x, warp = tid >> 5, lane = tid & 31;
    const int tile = blockIdx.x;
    const uint32_t bar_full = sb + BAR_OFF, bar_empty = bar_full + 8 * NST, bar_x = bar_empty + 8 * NST, bar_idx = bar_x + 32, bar_c = bar_idx + 8, bar_cand = bar_c + 8, bar_rest = bar_cand + 8;
    const __nv_bfloat16* __restrict__ e_attr = P.e_attr;

    int4 dv, sv;
    if (warp < 16) {
        if (tid < EPC / 4) {
            asm volatile("ld.global.nc.v4.s32 {%0,%1,%2,%3}, [%4];" : "=r"(dv.x), "=r"(dv.y), "=r"(dv.z), "=r"(dv.w)
                         : "l"((const int4*)P.dst + tile * (EPC / 4) + tid));
            asm volatile("ld.global.nc.v4.s32 {%0,%1,%2,%3}, [%4];" : "=r"(sv.x), "=r"(sv.y), "=r"(sv.z), "=r"(sv.w)
                         : "l"((const int4*)P.src + tile * (EPC / 4) + tid));
        }
        sts128(sb + CAND_OFF + tid * 16, make_uint4(REC_INV, REC_INV, REC_INV, REC_INV));
        sts128(sb + CAND_OFF + (tid + 512) * 16, make_uint4(REC_INV, REC_INV, REC_INV, REC_INV));
        if (tid < 128) sts32(sb + CNT_OFF + tid * 4, 0);
    } else if (warp < 20) {
        if (tid < N_MAIN + 16) sts32(sb + GCNT + (tid - N_MAIN) * 4, 0);
    } else if (tid == 640) {
        asm volatile("prefetch.tensormap [%0];" ::"l"(&tm_g) : "memory");
#pragma unroll
        for (int s = 0; s < NST; s++) {
            mbar_init(bar_full + 8 * s, 1);
            mbar_init(bar_empty + 8 * s, 16);
        }
        asm volatile("fence.mbarrier_init.release.cluster;" ::: "memory");
#pragma unroll 1
        for (int it = 0; it < NST; it++) {
            mbar_expect_tx(bar_full + 8 * it, 32768);
            tma_3d(sb + RING_OFF + it * 32768, &tm_g, 0, 256 + it * 64, 0, bar_full + 8 * it);
        }
    } else if (tid == 704) {
        asm volatile("prefetch.tensormap [%0];" ::"l"(&tm_x) : "memory");
#pragma unroll
        for (int s = 0; s < 4; s++) mbar_init(bar_x + 8 * s, 1);
        mbar_init(bar_idx, EPC / 128);
        mbar_init(bar_c, 1);
        mbar_init(bar_cand, 1);
        mbar_init(bar_rest, 4);
        asm volatile("fence.mbarrier_init.release.cluster;" ::: "memory");
#pragma unroll 1
        for (int c = 0; c < X_EARLY; c++) {
            mbar_expect_tx(bar_x + 8 * c, 10240);
            tma_2d(sb + X_OFF + c * 10240, &tm_x, c * 64, tile * TILE, bar_x + 8 * c);
        }
    } else if (tid == 672) {
        asm volatile("prefetch.tensormap [%0];" ::"l"(&tm_v) : "memory");
        asm volatile("prefetch.tensormap [%0];" ::"l"(&tm_u) : "memory");
        asm volatile("prefetch.tensormap [%0];" ::"l"(&tm_t) : "memory");
        asm volatile("prefetch.tensormap [%0];" ::"l"(&tm_c) : "memory");
        asm volatile("prefetch.tensormap [%0];" ::"l"(&tm_s) : "memory");
        asm volatile("prefetch.tensormap [%0];" ::"l"(&tm_s2) : "memory");
        const int go = tile * 2176, vo = tile * 1056;
        const int gn = min(2176, 528 * 512 - go), vn = min(1056, 256 * 512 - vo);
        if (gn > 0) asm volatile("cp.async.bulk.prefetch.L2.global [%0], %1;" ::"l"((const char*)P.g_w + go), "r"(gn) : "memory");
        if (vn > 0) {
            asm volatile("cp.async.bulk.prefetch.L2.global [%0], %1;" ::"l"((const char*)P.v_w + vo), "r"(vn) : "memory");
            asm volatile("cp.async.bulk.prefetch.L2.global [%0], %1;" ::"l"((const char*)P.u_w + vo), "r"(vn) : "memory");
        }
    }
    __syncthreads();

    if (warp >= 20) {
        asm volatile("setmaxnreg.dec.sync.aligned.u32 24;");
        if (tid == 640) {
            int st = 0, par = 0;
#pragma unroll 1
            for (int it = NST; it < NIT; it++) {
                const int p = it >> 2;
                const CUtensorMap* m = (p == 1) ? &tm_v : (p == 3) ? &tm_u : &tm_g;
                const int row = ((p == 0) ? 256 : 0) + (it & 3) * 64;
                mbar_wait(bar_empty + 8 * st, par);
                mbar_expect_tx(bar_full + 8 * st, 32768);
                tma_3d(sb + RING_OFF + st * 32768, m, 0, row, 0, bar_full + 8 * st);
                if (++st == NST) { st = 0; par ^= 1; }
            }
            mbar_wait(bar_empty + 8 * 1, 0);
            mbar_expect_tx(bar_c, 8192);
            tma_3d(sb + CT_OFF, &tm_c, 0, 512, 0, bar_c);
        } else if (tid == 704) {
            if (X_EARLY < 4) mbar_wait(bar_idx, 0);
#pragma unroll 1
            for (int c = X_EARLY; c < 4; c++) {
                mbar_expect_tx(bar_x + 8 * c, 10240);
                tma_2d(sb + X_OFF + c * 10240, &tm_x, c * 64, tile * TILE, bar_x + 8 * c);
            }
        } else if (warp == 21) {
            mbar_wait(bar_x + 8 * 3, 0);
#pragma unroll 1
            for (int i = lane; i < EPC * 32 / 128; i += 32)
                asm volatile("prefetch.global.L2 [%0];" ::"l"((const char*)e_attr + (size_t)tile * EPC * 32 + i * 128) : "memory");
        } else if (warp == 23) {
            unsigned int target = 0;
            if (lane == 0) target = grid_target(P.bar);
#pragma unroll 1
            for (int wave = 0; wave < 2; wave++) {
                bar_sync(BAR_TABLE, N_MAIN + 32);
                if (lane == 0) {
#pragma unroll 1
                    for (int ds = 0; ds < 8; ds++) {
                        asm volatile("cp.async.bulk.tensor.2d.global.shared::cta.bulk_group [%0, {%2, %3}], [%1];"
                                     ::"l"(&tm_t), "r"(sb + EATTR_OFF + ds * 5120), "r"(ds * 64), "r"(tile * TILE + wave * 40) : "memory");
                        asm volatile("cp.async.bulk.commit_group;" ::: "memory");
                        asm volatile("cp.async.bulk.wait_group.read %0;" ::"n"(STORE_QUEUE) : "memory");
                    }
                    asm volatile("cp.async.bulk.wait_group.read 0;" ::: "memory");
                }
                __syncwarp();
                if (wave == 0) bar_arrive(BAR_STG, N_MAIN + 32);
                else bar_arrive(BAR_XFREE, N_AUX + 32);
            }
            if (lane == 0) {
                asm volatile("cp.async.bulk.wait_group 0;" ::: "memory");
                grid_arrive_relaxed(P.bar);
                grid_wait(P.bar, target);
            }
            __syncwarp();
            bar_arrive(BAR_GO, N_MAIN + 32);
        }
    } else if (warp >= 16) {
        asm volatile("setmaxnreg.dec.sync.aligned.u32 40;");
        const int t = tid - N_MAIN;
        unsigned int target = 0;
        if (t == 0) target = grid_target(P.bar + 32);
        bar_sync(BAR_S1, N_MAIN + N_AUX);
        if (t == 0) {
            asm volatile("cp.async.bulk.tensor.3d.global.shared::cta.bulk_group [%0, {%2, %3, %2}], [%1];"
                         ::"l"(&tm_s), "r"(sb + CAND_OFF), "r"(0), "r"(tile) : "memory");
            asm volatile("cp.async.bulk.commit_group;" ::: "memory");
            asm volatile("cp.async.bulk.wait_group 0;" ::: "memory");
            grid_arrive_relaxed(P.bar + 32);
            grid_wait(P.bar + 32, target);
            asm volatile("fence.proxy.async.global;" ::: "memory");
            mbar_expect_tx(bar_cand, NT * 128);
            asm volatile("cp.async.bulk.tensor.4d.shared::cluster.global.mbarrier::complete_tx::bytes [%0], [%1, {%3, %3, %3, %4}], [%2];"
                         ::"r"(sb + CAND_OFF), "l"(&tm_s2), "r"(bar_cand), "r"(0), "r"(tile) : "memory");
        }
        const uint32_t row = sb + CAND_OFF + t * 32;
        mbar_wait(bar_cand, 0);
        bool ovf = false;
#pragma unroll 1
        for (int j = 0; j < 4; j++) {
            uint4 a = make_uint4(REC_INV, REC_INV, REC_INV, REC_INV), b = a;
            if (t < NT) { a = lds128(row + j * (NT * 32)); b = lds128(row + j * (NT * 32) + 16); }
            if (j >= 2 && !__any_sync(0xffffffffu, rec_dl(a.x) != 127)) break;
            const uint32_t rec[8] = {a.x, a.y, a.z, a.w, b.x, b.y, b.z, b.w};
            uint32_t rank[8];
#pragma unroll
            for (int i = 0; i < 8; i++) rank[i] = bin_rank(sb, rec[i]);
#pragma unroll
            for (int i = 0; i < 8; i++) bin_store(sb, rec[i], rank[i], t);
            ovf |= rec_dl(b.w) == 126;
        }
        ovf = bar_or(BAR_AUX, N_AUX, ovf);
        int run = ovf ? -1 : layout_list(sb, t, 1);
        if (run >= 0) {
            bar_sync(BAR_AUX, N_AUX);
            expand_meta(sb, t, run);
            bar_arrive(BAR_META, N_MAIN + N_AUX);
            bar_sync(BAR_AUX, N_AUX);
            bar_sync(BAR_XFREE, N_AUX + 32);
            gather_attr(sb, t, run, e_attr, bar_rest);
        } else {
            bar_sync(BAR_AUX, N_AUX);
            if (t < 16) sts32(sb + GCNT + t * 4, 0);
            bar_sync(BAR_AUX, N_AUX);
            bool first = true;
#pragma unroll 1
            for (int w0 = 0; w0 < NT * EPC; w0 += 128) {
                const int e = w0 + t, d = __ldg(P.dst + e), b = (unsigned)d / TILE;
                uint32_t w = REC_INV;
                const int c = (unsigned)e / EPC;
                if (b == tile) w = ((uint32_t)(d - b * TILE) << 24) | (__ldg(P.src + e) * EPC + (e - c * EPC));
                bin_store(sb, w, bin_rank(sb, w), c);
                bar_sync(BAR_AUX, N_AUX);
                int mx = 0, sum = 0;
#pragma unroll 1
                for (int g = 0; g < 10; g++) { const int v = lds32(sb + GCNT + g * 4); mx = max(mx, v); sum += v; }
                const bool fin = w0 + 128 >= NT * EPC;
                const bool flush = fin || mx > CAPG - 128 || sum > CAP_STEPS * 16 - 48 - 150 - 128;
                bar_sync(BAR_AUX, N_AUX);
                if (flush) {
                    if (first) bar_sync(BAR_XFREE, N_AUX + 32);
                    first = false;
                    run = layout_list(sb, t, fin);
                    bar_sync(BAR_AUX, N_AUX);
                    expand_meta(sb, t, run);
                    bar_arrive(BAR_META, N_MAIN + N_AUX);
                    bar_sync(BAR_AUX, N_AUX);
                    gather_attr(sb, t, run, e_attr, bar_rest);
                    if (!fin) bar_sync(BAR_CONSUMED, N_MAIN + N_AUX);
                    bar_sync(BAR_AUX, N_AUX);
                    if (t < 16) sts32(sb + GCNT + t * 4, 0);
                    bar_sync(BAR_AUX, N_AUX);
                }
            }
        }
    } else {
        asm volatile("setmaxnreg.inc.sync.aligned.u32 104;");
        const int wg = warp >> 2;
        const int r = lane >> 2, q = lane & 3;
        if (tid < EPC / 4) {
            const int dd[4] = {dv.x, dv.y, dv.z, dv.w};
            const int ss[4] = {sv.x, sv.y, sv.z, sv.w};
            uint32_t rank[4];
            int bb[4];
#pragma unroll
            for (int i = 0; i < 4; i++) {
                bb[i] = (unsigned)dd[i] / TILE;
                asm volatile("atom.shared.add.u32 %0, [%1], 1;" : "=r"(rank[i]) : "r"(sb + CNT_OFF + bb[i] * 4) : "memory");
            }
#pragma unroll
            for (int i = 0; i < 4; i++) {
                const uint32_t rec = ((uint32_t)(dd[i] - bb[i] * TILE) << 24) | (ss[i] * EPC + tid * 4 + i);
                sts32(sb + CAND_OFF + bb[i] * 128 + (min(rank[i], 31u) << 2), rank[i] < 31 ? rec : REC_OVF);
            }
            __syncwarp();
            if (lane == 0) mbar_arrive(bar_idx);
        }
        asm volatile("fence.proxy.async.shared::cta;" ::: "memory");
        bar_arrive(BAR_S1, N_MAIN + N_AUX);

        float d[40];
        uint32_t pB[20], pV[20], xa[20];
        const uint64_t da0 = smem_desc(sb + RING_OFF + wg * 8192), db0 = smem_desc(sb + X_OFF);

        auto stage = [&](const int it) {
            const int c = it & 3, st = it % NST;
            if (it < 4) mbar_wait(bar_x + 8 * c, 0);
            mbar_wait(bar_full + 8 * st, (it / NST) & 1);
            wgmma_fence();
            const uint64_t da = da0 + st * 2048, db = db0 + c * 640;
            wgmma_n80(d, da, db, c != 0);
            wgmma_n80(d, da + 128, db + 2, 1);
            wgmma_n80(d, da + 256, db + 4, 1);
            wgmma_n80(d, da + 384, db + 6, 1);
            wgmma_commit();
        };
        auto release = [&](const int it) {
            if ((it + NST < NIT || it == 13) && lane == 0) mbar_arrive(bar_empty + 8 * (it % NST));
        };

        auto stage_table = [&](const int wave) {
            const uint32_t base = sb + EATTR_OFF + (warp >> 1) * 5120 + (lane & 7) * 128 +
                                  ((((warp & 1) * 4 + (lane >> 3)) ^ (lane & 7)) << 4);
#pragma unroll
            for (int jj = 0; jj < 5; jj++) {
                const int j = (wave * 5 + jj) * 2;
                asm volatile("stmatrix.sync.aligned.m8n8.x4.trans.shared.b16 [%0], {%1,%2,%3,%4};"
                             ::"r"(base + jj * 1024), "r"(pB[j]), "r"(pB[j + 1]), "r"(pV[j]), "r"(pV[j + 1]) : "memory");
            }
            asm volatile("fence.proxy.async.shared::cta;" ::: "memory");
            bar_arrive(BAR_TABLE, N_MAIN + 32);
        };
#pragma unroll
        for (int p = 0; p < 4; p++) {
#pragma unroll
            for (int c = 0; c < 4; c++) {
                stage(p * 4 + c);
                if (p == 2 && c == 0) stage_table(0);
                if (p * 4 + c == WAVE2_TILE) { bar_sync(BAR_STG, N_MAIN + 32); stage_table(1); }
                if (c > 0) { wgmma_wait<1>(); release(p * 4 + c - 1); }
            }
            wgmma_wait<0>();
            release(p * 4 + 3);
            if (p == 0) {
#pragma unroll
                for (int j = 0; j < 20; j++) pB[j] = pack_bf16(0.5f * d[2 * j], 0.5f * d[2 * j + 1]);
            } else if (p == 1) {
#pragma unroll
                for (int j = 0; j < 20; j++) pV[j] = pack_bf16(0.5f * d[2 * j], 0.5f * d[2 * j + 1]);
            } else if (p == 2) {
#pragma unroll
                for (int j = 0; j < 20; j++) xa[j] = pack_bf16(0.5f * d[2 * j], 0.5f * d[2 * j + 1]);
            }
        }

        uint32_t cf[2][4];
        mbar_wait(bar_c, 0);
#pragma unroll
        for (int c = 0; c < 2; c++) {
            const int k = (lane >> 4) * 8 + (lane & 7), col = (warp & 7) * 32 + c * 16 + ((lane >> 3) & 1) * 8;
            asm volatile("ldmatrix.sync.aligned.m8n8.x4.trans.shared.b16 {%0,%1,%2,%3}, [%4];"
                         : "=r"(cf[c][0]), "=r"(cf[c][1]), "=r"(cf[c][2]), "=r"(cf[c][3])
                         : "r"(sb + CT_OFF + (col >> 6) * 2048 + k * 128 + ((((col & 63) >> 3) ^ (k & 7)) << 4)));
#pragma unroll
            for (int i = 0; i < 4; i++) asm("mul.rn.bf16x2 %0, %0, %1;" : "+r"(cf[c][i]) : "r"(0x3F003F00u));
        }
        bar_sync(BAR_MAIN, N_MAIN);
#pragma unroll
        for (int j = 0; j < 10; j++) {
            asm volatile("st.shared.v2.u32 [%0], {%1, %2};" ::"r"(sb + PARK_U + (warp * 10 + j) * 256 + lane * 8),
                         "r"(pack_bf16(d[4 * j], d[4 * j + 1])), "r"(pack_bf16(d[4 * j + 2], d[4 * j + 3])) : "memory");
            asm volatile("st.shared.v2.u32 [%0], {%1, %2};" ::"r"(sb + PARK_XA + (warp * 10 + j) * 256 + lane * 8), "r"(xa[2 * j]), "r"(xa[2 * j + 1]) : "memory");
        }
        bar_sync(BAR_MAIN, N_MAIN);

        {
            const int ds = warp & 7, set = warp >> 3;
            const uint32_t cA = bf16_bits_of_int(2 * q) | (bf16_bits_of_int(2 * q + 1) << 16);
            const uint32_t cB = bf16_bits_of_int(r) * 0x10001u;
            uint32_t id0, id1, id2, id3;
            {
                const uint32_t v = (r == 2 * q ? 0x00003F80u : 0u) | (r == 2 * q + 1 ? 0x3F800000u : 0u);
                asm volatile("mov.u32 %0, %4;\nmov.u32 %1, 0;\nmov.u32 %2, 0;\nmov.u32 %3, %4;" : "=r"(id0), "=r"(id1), "=r"(id2), "=r"(id3) : "r"(v));
            }
            const char* tabl = (const char*)P.tab + ds * 128 + (lane & 7) * 16;
            const int ek = (lane >> 4) * 8 + (lane & 7);
            const uint32_t ea_l = sb + EATTR_OFF + ek * 32 + ((((lane >> 3) & 1) ^ ((ek >> 2) & 1)) << 4);
            const uint32_t mr_l = sb + MR_OFF + r * 16;
            const uint32_t mq_l = sb + MQ_OFF + q * 8;
            const uint32_t bounce = sb + CAND_OFF + warp * 512;
            const uint32_t pk = sb + (ds * 20 + set * 5) * 256 + lane * 8;
            float4* const part = P.part + ((size_t)tile * 160 + ds * 20 + set * 5) * 32 + lane;

            const uint32_t yb = warp < 14 ? sb + YB_OFF + warp * 4096 : sb + CAND_OFF + 8192 + (warp - 14) * 4096;
            const int g8 = lane >> 3;
            const uint32_t y_dst = yb + g8 * 128 + (((lane & 7) ^ g8) << 4);
            const uint32_t y_dst2 = yb + (g8 + 4) * 128 + (((lane & 7) ^ (g8 + 4)) << 4);
            const uint32_t mw_l = sb + MR_OFF + g8 * 16;
            const uint32_t y_ldb = yb + (lane & 7) * 128 + (((((lane >> 3) & 1) + (lane >> 4) * 4) ^ (lane & 7)) << 4);
            const uint32_t y_ldv = y_ldb ^ 32;

            auto gather1 = [&](uint32_t dst, uint32_t w) {
                asm volatile("{\n.reg .pred p;\n.reg .b64 a;\nsetp.ge.s32 p, %1, 0;\nmad.wide.u32 a, %1, 1024, %2;\n"
                             "@p cp.async.cg.shared.global [%0], [a], 16;\n}" ::"r"(dst), "r"(w), "l"(tabl) : "memory");
            };

            bar_sync(BAR_GO, N_MAIN + 32);
            for (int pass = 0;; pass++) {
                bar_sync(BAR_META, N_MAIN + N_AUX);
                const int last = lds32(sb + MISC_OFF + 44);
                int i = set ? (int)lds32(sb + MISC_OFF + 40) : 0;
                uint32_t pe = ea_l + i * 512, pr = mr_l + i * 128, pq = mq_l + i * 32;
                auto gather_step = [&](const int k, const int off) {
                    const uint32_t pw = pr - mr_l + mw_l + off;
                    const uint2 wa = lds64(pw), wb = lds64(pw + 64);
                    gather1(y_dst + k * 2048, wa.x);
                    gather1(y_dst2 + k * 2048, wb.x);
                    gather1(y_dst + k * 2048 + 1024, wa.y);
                    gather1(y_dst2 + k * 2048 + 1024, wb.y);
                    asm volatile("cp.async.commit_group;" ::: "memory");
                };
                {
#pragma unroll
                    for (int k = 0; k < 8; k++) sts128(yb + lane * 16 + k * 512, make_uint4(0, 0, 0, 0));
                    __syncwarp();
                    gather_step(0, 0);
                    gather_step(1, 128);
                }
                uint32_t xb[2][4], hv[2][4];
                auto fetch = [&](const int k, const int off) {
                    asm volatile("cp.async.wait_group 1;" ::: "memory");
                    __syncwarp();
#pragma unroll
                    for (int t = 0; t < 2; t++) {
                        asm volatile("ldmatrix.sync.aligned.m8n8.x4.shared.b16 {%0,%1,%2,%3}, [%4];"
                                     : "=r"(xb[t][0]), "=r"(xb[t][1]), "=r"(xb[t][2]), "=r"(xb[t][3]) : "r"(y_ldb + k * 2048 + t * 1024) : "memory");
                        asm volatile("ldmatrix.sync.aligned.m8n8.x4.trans.shared.b16 {%0,%1,%2,%3}, [%4];"
                                     : "=r"(hv[t][0]), "=r"(hv[t][1]), "=r"(hv[t][2]), "=r"(hv[t][3]) : "r"(y_ldv + k * 2048 + t * 1024) : "memory");
                    }
                    gather_step(k, off);
                };
                fetch(0, 2 * 128);
                bar_sync(BAR_READY, N_MAIN + N_AUX);
                int ph = 0;
                for (int g = 0; g < 5; g++) {
                    const int gend = lds32(sb + MISC_OFF + (set * 5 + g) * 4);
                    float acc[2][4];
                    uint2 xf[2];
#pragma unroll
                    for (int c = 0; c < 2; c++) {
                        if (pass == 0) {
                            const uint2 u = lds64(pk + PARK_U + (c * 10 + g) * 256);
                            acc[c][0] = __uint_as_float(u.x << 16); acc[c][1] = __uint_as_float(u.x & 0xFFFF0000u);
                            acc[c][2] = __uint_as_float(u.y << 16); acc[c][3] = __uint_as_float(u.y & 0xFFFF0000u);
                        } else {
                            const float4 a = part[(c * 10 + g) * 32];
                            acc[c][0] = a.x; acc[c][1] = a.y; acc[c][2] = a.z; acc[c][3] = a.w;
                        }
                        xf[c] = lds64(pk + PARK_XA + (c * 10 + g) * 256);
                    }

                    auto step = [&](const int k) {
                        const uint2 dd = lds64(pr + k * 128 + 8);
                        const uint2 db = lds64(pq + k * 32);
                        uint32_t e[4];
                        asm volatile("ldmatrix.sync.aligned.m8n8.x4.shared.b16 {%0,%1,%2,%3}, [%4];"
                                     : "=r"(e[0]), "=r"(e[1]), "=r"(e[2]), "=r"(e[3]) : "r"(pe + k * 512));
                        const uint32_t sa0 = seteq_bf16x2(dd.x, cA), sa1 = seteq_bf16x2(dd.y, cA);
                        const uint32_t sb0 = seteq_bf16x2(db.x, cB), sb1 = seteq_bf16x2(db.y, cB);
#pragma unroll
                        for (int c = 0; c < 2; c++) {
                            float p0[4], p1[4];
                            mma_bf16(p0, cf[c][0], cf[c][1], cf[c][2], cf[c][3], e[0], e[1], 0.f, 0.f, 0.f, 0.f);
                            mma_bf16(p1, cf[c][0], cf[c][1], cf[c][2], cf[c][3], e[2], e[3], 0.f, 0.f, 0.f, 0.f);
                            mma_bf16_k8(p0, xf[c].x, xf[c].y, sa0);
                            mma_bf16_k8(p1, xf[c].x, xf[c].y, sa1);
                            mma_bf16(p0, id0, id1, id2, id3, xb[0][2 * c], xb[0][2 * c + 1], p0[0], p0[1], p0[2], p0[3]);
                            mma_bf16(p1, id0, id1, id2, id3, xb[1][2 * c], xb[1][2 * c + 1], p1[0], p1[1], p1[2], p1[3]);
                            const uint32_t m0 = fma_bf16x2(hv[0][2 * c], pack_bf16(tanh_approx(p0[0]), tanh_approx(p0[1])), hv[0][2 * c]);
                            const uint32_t m1 = fma_bf16x2(hv[0][2 * c + 1], pack_bf16(tanh_approx(p0[2]), tanh_approx(p0[3])), hv[0][2 * c + 1]);
                            const uint32_t m2 = fma_bf16x2(hv[1][2 * c], pack_bf16(tanh_approx(p1[0]), tanh_approx(p1[1])), hv[1][2 * c]);
                            const uint32_t m3 = fma_bf16x2(hv[1][2 * c + 1], pack_bf16(tanh_approx(p1[2]), tanh_approx(p1[3])), hv[1][2 * c + 1]);
                            mma_bf16(acc[c], m0, m1, m2, m3, sb0, sb1, acc[c][0], acc[c][1], acc[c][2], acc[c][3]);
                        }
                        fetch(k ^ 1, (k + 3) * 128);
                    };

                    int rem = gend - i;
                    i = gend;
                    while (rem > 0) {
                        if (ph == 0) {
                            step(0);
                            ph = 1;
                            if (--rem == 0) break;
                        }
                        step(1);
                        ph = 0; pe += 2 * 512; pr += 2 * 128; pq += 2 * 32; --rem;
                    }

                    if (g == 0) mbar_wait(bar_rest, pass & 1);

                    if (last) {
                        uint32_t o[4];
#pragma unroll
                        for (int c = 0; c < 2; c++) {
                            float z[4];
#pragma unroll
                            for (int j = 0; j < 4; j++) z[j] = __fdividef(acc[c][j], 1.f + __expf(-acc[c][j]));
                            o[2 * c] = pack_bf16(z[0], z[1]);
                            o[2 * c + 1] = pack_bf16(z[2], z[3]);
                        }
                        asm volatile("stmatrix.sync.aligned.m8n8.x4.trans.shared.b16 [%0], {%1,%2,%3,%4};"
                                     ::"r"(bounce + (lane & 7) * 64 + (((lane >> 3) ^ ((lane >> 1) & 3)) << 4)),
                                       "r"(o[0]), "r"(o[1]), "r"(o[2]), "r"(o[3]) : "memory");
                        __syncwarp();
                        const int node = lane >> 2;
                        const uint4 v = lds128(bounce + node * 64 + ((q ^ ((node >> 1) & 3)) << 4));
                        *(uint4*)(P.out + (size_t)(tile * TILE + (set * 5 + g) * 8 + node) * DD + ds * 32 + q * 8) = v;
                        __syncwarp();
                    } else {
#pragma unroll
                        for (int c = 0; c < 2; c++) part[(c * 10 + g) * 32] = make_float4(acc[c][0], acc[c][1], acc[c][2], acc[c][3]);
                    }
                }
                if (last) break;
                cp_async_wait_all();
                bar_arrive(BAR_CONSUMED, N_MAIN + N_AUX);
            }
        }
    }
}

typedef CUresult (*EncodeFn)(CUtensorMap*, CUtensorMapDataType, cuuint32_t, void*, const cuuint64_t*, const cuuint64_t*,
                             const cuuint32_t*, const cuuint32_t*, CUtensorMapInterleave, CUtensorMapSwizzle,
                             CUtensorMapL2promotion, CUtensorMapFloatOOBfill);

static void make_map(EncodeFn fn, CUtensorMap* m, const void* ptr, int rows, int box_rows) {
    cuuint64_t dims[2] = {(cuuint64_t)DD, (cuuint64_t)rows};
    cuuint64_t strides[1] = {(cuuint64_t)DD * 2};
    cuuint32_t box[2] = {64, (cuuint32_t)box_rows};
    cuuint32_t es[2] = {1, 1};
    fn(m, CU_TENSOR_MAP_DATA_TYPE_BFLOAT16, 2, const_cast<void*>(ptr), dims, strides, box, es, CU_TENSOR_MAP_INTERLEAVE_NONE,
       CU_TENSOR_MAP_SWIZZLE_128B, CU_TENSOR_MAP_L2_PROMOTION_L2_256B, CU_TENSOR_MAP_FLOAT_OOB_FILL_NONE);
}

static void make_tmap(EncodeFn fn, CUtensorMap* m, void* ptr) {
    cuuint64_t dims[2] = {512, (cuuint64_t)NN};
    cuuint64_t strides[1] = {1024};
    cuuint32_t box[2] = {64, 40};
    cuuint32_t es[2] = {1, 1};
    fn(m, CU_TENSOR_MAP_DATA_TYPE_BFLOAT16, 2, ptr, dims, strides, box, es, CU_TENSOR_MAP_INTERLEAVE_NONE,
       CU_TENSOR_MAP_SWIZZLE_128B, CU_TENSOR_MAP_L2_PROMOTION_NONE, CU_TENSOR_MAP_FLOAT_OOB_FILL_NONE);
}

static void make_smap(EncodeFn fn, CUtensorMap* m, void* ptr) {
    cuuint64_t dims[3] = {32, (cuuint64_t)NT, (cuuint64_t)NT};
    cuuint64_t strides[2] = {128, (cuuint64_t)NT * 128};
    cuuint32_t box[3] = {32, 1, (cuuint32_t)NT};
    cuuint32_t es[3] = {1, 1, 1};
    fn(m, CU_TENSOR_MAP_DATA_TYPE_UINT32, 3, ptr, dims, strides, box, es, CU_TENSOR_MAP_INTERLEAVE_NONE,
       CU_TENSOR_MAP_SWIZZLE_NONE, CU_TENSOR_MAP_L2_PROMOTION_NONE, CU_TENSOR_MAP_FLOAT_OOB_FILL_NONE);
}

static void make_smap2(EncodeFn fn, CUtensorMap* m, void* ptr) {
    cuuint64_t dims[4] = {8, (cuuint64_t)NT, 4, (cuuint64_t)NT};
    cuuint64_t strides[3] = {128, 32, (cuuint64_t)NT * 128};
    cuuint32_t box[4] = {8, (cuuint32_t)NT, 4, 1};
    cuuint32_t es[4] = {1, 1, 1, 1};
    fn(m, CU_TENSOR_MAP_DATA_TYPE_UINT32, 4, ptr, dims, strides, box, es, CU_TENSOR_MAP_INTERLEAVE_NONE,
       CU_TENSOR_MAP_SWIZZLE_NONE, CU_TENSOR_MAP_L2_PROMOTION_NONE, CU_TENSOR_MAP_FLOAT_OOB_FILL_NONE);
}

static void make_wmap(EncodeFn fn, CUtensorMap* m, const void* ptr, int rows, int box_rows) {
    cuuint64_t dims[3] = {64, (cuuint64_t)rows, 4};
    cuuint64_t strides[2] = {(cuuint64_t)DD * 2, 128};
    cuuint32_t box[3] = {64, (cuuint32_t)box_rows, 4};
    cuuint32_t es[3] = {1, 1, 1};
    fn(m, CU_TENSOR_MAP_DATA_TYPE_BFLOAT16, 3, const_cast<void*>(ptr), dims, strides, box, es, CU_TENSOR_MAP_INTERLEAVE_NONE,
       CU_TENSOR_MAP_SWIZZLE_128B, CU_TENSOR_MAP_L2_PROMOTION_L2_256B, CU_TENSOR_MAP_FLOAT_OOB_FILL_NONE);
}

}

extern "C" void kernel_launch(void* const* d_in, const int* in_sizes, int n_in, void* d_out, int out_size) {
    using namespace egc;
    (void)in_sizes; (void)n_in; (void)out_size;
    static EncodeFn encode = nullptr;
    static void *p_tab = nullptr, *p_slots = nullptr, *p_bar = nullptr, *p_part = nullptr;
    if (!encode) {
        void* fn = nullptr;
        cudaDriverEntryPointQueryResult qr;
        cudaGetDriverEntryPoint("cuTensorMapEncodeTiled", &fn, cudaEnableDefault, &qr);
        encode = (EncodeFn)fn;
        cudaFuncSetAttribute(egc_kernel, cudaFuncAttributeMaxDynamicSharedMemorySize, SMEM_BYTES);
        cudaGetSymbolAddress(&p_tab, g_tab);
        cudaGetSymbolAddress(&p_slots, g_slots);
        cudaGetSymbolAddress(&p_bar, g_bar);
        cudaGetSymbolAddress(&p_part, g_part);
    }
    const __nv_bfloat16* x = (const __nv_bfloat16*)d_in[0];
    Params P;
    P.e_attr = (const __nv_bfloat16*)d_in[1];
    P.src = (const int*)d_in[2];
    P.dst = (const int*)d_in[3];
    P.u_w = (const __nv_bfloat16*)d_in[4];
    P.v_w = (const __nv_bfloat16*)d_in[5];
    P.g_w = (const __nv_bfloat16*)d_in[6];
    P.out = (__nv_bfloat16*)d_out;
    P.tab = (uint4*)p_tab;
    P.slots = (uint4*)p_slots;
    P.bar = (unsigned int*)p_bar;
    P.part = (float4*)p_part;
    CUtensorMap tx, tg, tv, tu, tt, tc, ts, ts2;
    make_smap(encode, &ts, p_slots);
    make_smap2(encode, &ts2, p_slots);
    make_tmap(encode, &tt, p_tab);
    make_map(encode, &tx, x, NN, TILE);
    make_wmap(encode, &tg, P.g_w, 2 * DD + 16, 64);
    make_wmap(encode, &tc, P.g_w, 2 * DD + 16, 16);
    make_wmap(encode, &tv, P.v_w, DD, 64);
    make_wmap(encode, &tu, P.u_w, DD, 64);
    egc_kernel<<<NT, NTHREADS, SMEM_BYTES, cudaStreamPerThread>>>(tx, tg, tv, tu, tt, tc, ts, ts2, P);
}
```

```cpp
#include <cuda_runtime.h>
#include <cuda_bf16.h>
#include <cuda.h>
#include <stdint.h>

namespace egc {

constexpr int NN = 10000;
constexpr int DD = 256;
constexpr int TILE = 80;
constexpr int NT = 125;
constexpr int EPC = 1280;
constexpr int NST = 3;
constexpr int NIT = 16;
constexpr int WAIT_HINT_NS = 20000;
constexpr int STORE_QUEUE = 3;
constexpr int X_EARLY = 3;
constexpr int CAP_STEPS = 98;

constexpr int N_MAIN = 512, N_AUX = 128;
constexpr int NTHREADS = N_MAIN + N_AUX + 128;

constexpr int X_OFF = 0;
constexpr int RING_OFF = 40960;
constexpr int PARK_U = 0;
constexpr int PARK_XA = 40960;
constexpr int YB_OFF = 81920;
constexpr int EATTR_OFF = RING_OFF + NST * 32768;
constexpr int CT_OFF = EATTR_OFF + 40960;
constexpr int CAND_OFF = EATTR_OFF + CAP_STEPS * 512;
constexpr int MR_OFF = CAND_OFF + 16384;
constexpr int MQ_OFF = MR_OFF + (CAP_STEPS + 3) * 128;
constexpr int CAPG = 192;
constexpr int EL_OFF = MQ_OFF + CAP_STEPS * 32;
constexpr int ER_OFF = EL_OFF + 10 * CAPG * 4;
constexpr int CNT_OFF = ER_OFF + 10 * CAPG;
constexpr int MISC_OFF = CNT_OFF + 512;
constexpr int BAR_OFF = MISC_OFF + 128;
constexpr int SMEM_BYTES = BAR_OFF + 128;
static_assert(YB_OFF + 14 * 4096 <= EATTR_OFF, "park area and gather buffers must fit in x + ring");
static_assert(CT_OFF + 8192 <= CAND_OFF && CT_OFF % 1024 == 0, "C tile placement");
static_assert(SMEM_BYTES <= 232448, "too much shared memory");

constexpr uint32_t REC_INV = 0x7FFFFFFFu, REC_OVF = 0x7E000000u;
__device__ __forceinline__ uint32_t rec_dl(uint32_t w) { return (w >> 24) & 127; }
constexpr uint32_t DBF_INV = 0x4380u;

constexpr int BAR_AUX = 1, BAR_MAIN = 2, BAR_READY = 3, BAR_CONSUMED = 4, BAR_TABLE = 5, BAR_GO = 6, BAR_S1 = 7, BAR_STG = 8, BAR_XFREE = 9, BAR_META = 10;

__device__ uint4 g_tab[(size_t)NN * 64];
__device__ float4 g_part[(size_t)NT * 160 * 32];
__device__ uint4 g_slots[(size_t)NT * NT * 8];
__device__ unsigned int g_bar[64];

__device__ __forceinline__ void bar_sync(int id, int n) { asm volatile("bar.sync %0, %1;" ::"r"(id), "r"(n) : "memory"); }
__device__ __forceinline__ void bar_arrive(int id, int n) { asm volatile("bar.arrive %0, %1;" ::"r"(id), "r"(n) : "memory"); }

__device__ __forceinline__ void mbar_init(uint32_t bar, uint32_t cnt) {
    asm volatile("mbarrier.init.shared::cta.b64 [%0], %1;" ::"r"(bar), "r"(cnt) : "memory");
}
__device__ __forceinline__ void mbar_expect_tx(uint32_t bar, uint32_t bytes) {
    asm volatile("mbarrier.arrive.expect_tx.shared::cta.b64 _, [%0], %1;" ::"r"(bar), "r"(bytes) : "memory");
}
__device__ __forceinline__ void mbar_arrive(uint32_t bar) {
    asm volatile("mbarrier.arrive.shared::cta.b64 _, [%0];" ::"r"(bar) : "memory");
}
__device__ __forceinline__ void mbar_wait(uint32_t bar, uint32_t parity) {
    uint32_t ok;
    int spins = 0;
    do {
        asm volatile("{\n.reg .pred p;\nmbarrier.try_wait.parity.shared::cta.b64 p, [%1], %2, %3;\nselp.u32 %0, 1, 0, p;\n}"
                     : "=r"(ok) : "r"(bar), "r"(parity), "r"(WAIT_HINT_NS) : "memory");
    } while (!ok && ++spins < (1 << 16));
}
__device__ __forceinline__ void tma_2d(uint32_t dst, const CUtensorMap* map, int c0, int c1, uint32_t bar) {
    asm volatile("cp.async.bulk.tensor.2d.shared::cluster.global.mbarrier::complete_tx::bytes [%0], [%1, {%3, %4}], [%2];"
                 ::"r"(dst), "l"(map), "r"(bar), "r"(c0), "r"(c1) : "memory");
}
__device__ __forceinline__ void tma_3d(uint32_t dst, const CUtensorMap* map, int c0, int c1, int c2, uint32_t bar) {
    asm volatile("cp.async.bulk.tensor.3d.shared::cluster.global.mbarrier::complete_tx::bytes [%0], [%1, {%3, %4, %5}], [%2];"
                 ::"r"(dst), "l"(map), "r"(bar), "r"(c0), "r"(c1), "r"(c2) : "memory");
}
__device__ __forceinline__ void sts32_if(bool p, uint32_t a, uint32_t v) {
    asm volatile("{\n.reg .pred p;\nsetp.ne.u32 p, %2, 0;\n@p st.shared.u32 [%0], %1;\n}" ::"r"(a), "r"(v), "r"((uint32_t)p) : "memory");
}
__device__ __forceinline__ void sts8_if(bool p, uint32_t a, uint32_t v) {
    asm volatile("{\n.reg .pred p;\nsetp.ne.u32 p, %2, 0;\n@p st.shared.u8 [%0], %1;\n}" ::"r"(a), "r"(v), "r"((uint32_t)p) : "memory");
}
__device__ __forceinline__ void cp_async_wait_all() { asm volatile("cp.async.wait_all;" ::: "memory"); }

__device__ __forceinline__ uint32_t lds32(uint32_t a) { uint32_t v; asm volatile("ld.shared.u32 %0, [%1];" : "=r"(v) : "r"(a)); return v; }
__device__ __forceinline__ uint2 lds64(uint32_t a) { uint2 v; asm volatile("ld.shared.v2.u32 {%0,%1}, [%2];" : "=r"(v.x), "=r"(v.y) : "r"(a)); return v; }
__device__ __forceinline__ uint4 lds128(uint32_t a) {
    uint4 v; asm volatile("ld.shared.v4.u32 {%0,%1,%2,%3}, [%4];" : "=r"(v.x), "=r"(v.y), "=r"(v.z), "=r"(v.w) : "r"(a)); return v;
}
__device__ __forceinline__ void sts16(uint32_t a, uint32_t v) { asm volatile("st.shared.u16 [%0], %1;" ::"r"(a), "h"((uint16_t)v) : "memory"); }
__device__ __forceinline__ void sts32(uint32_t a, uint32_t v) { asm volatile("st.shared.u32 [%0], %1;" ::"r"(a), "r"(v) : "memory"); }
__device__ __forceinline__ void sts128(uint32_t a, uint4 v) {
    asm volatile("st.shared.v4.u32 [%0], {%1,%2,%3,%4};" ::"r"(a), "r"(v.x), "r"(v.y), "r"(v.z), "r"(v.w) : "memory");
}
__device__ __forceinline__ uint32_t pack_bf16(float lo, float hi) {
    uint32_t d; asm("cvt.rn.bf16x2.f32 %0, %1, %2;" : "=r"(d) : "f"(hi), "f"(lo)); return d;
}
__device__ __forceinline__ uint32_t seteq_bf16x2(uint32_t a, uint32_t b) {
    uint32_t d; asm("set.eq.bf16x2.bf16x2 %0, %1, %2;" : "=r"(d) : "r"(a), "r"(b)); return d;
}
__device__ __forceinline__ uint32_t fma_bf16x2(uint32_t a, uint32_t b, uint32_t c) {
    uint32_t d; asm("fma.rn.bf16x2 %0, %1, %2, %3;" : "=r"(d) : "r"(a), "r"(b), "r"(c)); return d;
}
__device__ __forceinline__ float tanh_approx(float x) { float y; asm("tanh.approx.f32 %0, %1;" : "=f"(y) : "f"(x)); return y; }
__device__ __forceinline__ uint32_t bf16_bits_of_int(int v) { return __float_as_uint((float)v) >> 16; }

__device__ __forceinline__ void mma_bf16(float (&d)[4], uint32_t a0, uint32_t a1, uint32_t a2, uint32_t a3,
                                         uint32_t b0, uint32_t b1, float c0, float c1, float c2, float c3) {
    asm("mma.sync.aligned.m16n8k16.row.col.f32.bf16.bf16.f32 {%0,%1,%2,%3}, {%4,%5,%6,%7}, {%8,%9}, {%10,%11,%12,%13};"
        : "=f"(d[0]), "=f"(d[1]), "=f"(d[2]), "=f"(d[3])
        : "r"(a0), "r"(a1), "r"(a2), "r"(a3), "r"(b0), "r"(b1), "f"(c0), "f"(c1), "f"(c2), "f"(c3));
}

__device__ __forceinline__ void mma_bf16_k8(float (&d)[4], uint32_t a0, uint32_t a1, uint32_t b0) {
    asm("mma.sync.aligned.m16n8k8.row.col.f32.bf16.bf16.f32 {%0,%1,%2,%3}, {%4,%5}, {%6}, {%0,%1,%2,%3};"
        : "+f"(d[0]), "+f"(d[1]), "+f"(d[2]), "+f"(d[3]) : "r"(a0), "r"(a1), "r"(b0));
}

__device__ __forceinline__ void wgmma_n80(float (&d)[40], uint64_t da, uint64_t db, int scale_d) {
    asm volatile(
        "{\n.reg .pred p;\nsetp.ne.b32 p, %42, 0;\n"
        "wgmma.mma_async.sync.aligned.m64n80k16.f32.bf16.bf16 "
        "{%0,%1,%2,%3,%4,%5,%6,%7,%8,%9,%10,%11,%12,%13,%14,%15,%16,%17,%18,%19,"
        "%20,%21,%22,%23,%24,%25,%26,%27,%28,%29,%30,%31,%32,%33,%34,%35,%36,%37,%38,%39}, "
        "%40, %41, p, 1, 1, 1, 0;\n}"
        : "+f"(d[0]), "+f"(d[1]), "+f"(d[2]), "+f"(d[3]), "+f"(d[4]), "+f"(d[5]), "+f"(d[6]), "+f"(d[7]),
          "+f"(d[8]), "+f"(d[9]), "+f"(d[10]), "+f"(d[11]), "+f"(d[12]), "+f"(d[13]), "+f"(d[14]), "+f"(d[15]),
          "+f"(d[16]), "+f"(d[17]), "+f"(d[18]), "+f"(d[19]), "+f"(d[20]), "+f"(d[21]), "+f"(d[22]), "+f"(d[23]),
          "+f"(d[24]), "+f"(d[25]), "+f"(d[26]), "+f"(d[27]), "+f"(d[28]), "+f"(d[29]), "+f"(d[30]), "+f"(d[31]),
          "+f"(d[32]), "+f"(d[33]), "+f"(d[34]), "+f"(d[35]), "+f"(d[36]), "+f"(d[37]), "+f"(d[38]), "+f"(d[39])
        : "l"(da), "l"(db), "r"(scale_d));
}
__device__ __forceinline__ void wgmma_fence() { asm volatile("wgmma.fence.sync.aligned;" ::: "memory"); }
__device__ __forceinline__ void wgmma_commit() { asm volatile("wgmma.commit_group.sync.aligned;" ::: "memory"); }
template <int N> __device__ __forceinline__ void wgmma_wait() { asm volatile("wgmma.wait_group.sync.aligned %0;" ::"n"(N) : "memory"); }

__device__ __forceinline__ uint64_t smem_desc(uint32_t addr) {
    return (uint64_t)((addr & 0x3FFFF) >> 4) | ((uint64_t)1 << 16) | ((uint64_t)64 << 32) | ((uint64_t)1 << 62);
}

__device__ __forceinline__ unsigned int grid_target(const unsigned int* ctr) {
    unsigned int v;
    asm volatile("ld.relaxed.gpu.global.u32 %0, [%1];" : "=r"(v) : "l"(ctr) : "memory");
    return (v / NT + 1u) * NT;
}
__device__ __forceinline__ void grid_arrive_relaxed(unsigned int* ctr) {
    asm volatile("red.relaxed.gpu.global.add.u32 [%0], 1;" ::"l"(ctr) : "memory");
}
__device__ __forceinline__ void grid_wait(const unsigned int* ctr, unsigned int target) {
    unsigned int v;
    int spins = 0;
    do {
        asm volatile("ld.acquire.gpu.global.u32 %0, [%1];" : "=r"(v) : "l"(ctr) : "memory");
    } while ((int)(v - target) < 0 && ++spins < (1 << 21));
}

constexpr int GCNT = MISC_OFF + 64;

__device__ __forceinline__ uint32_t bin_rank(uint32_t sb, uint32_t w) {
    uint32_t rank;
    asm volatile("{\n.reg .pred p;\nsetp.lt.u32 p, %1, %3;\nmov.u32 %0, 0xFFFF;\n@p atom.shared.add.u32 %0, [%2], 1;\n}"
                 : "=r"(rank) : "r"(w >> 24), "r"(sb + GCNT + ((w >> 25) & 0x3C)), "n"(TILE) : "memory");
    return rank;
}
__device__ __forceinline__ void bin_store(uint32_t sb, uint32_t w, uint32_t rank, uint32_t row) {
    const uint32_t idx = (w >> 27) * CAPG + rank;
    sts32_if(rank < CAPG, sb + EL_OFF + idx * 4, w);
    sts8_if(rank < CAPG, sb + ER_OFF + idx, row);
}
__device__ __forceinline__ bool bar_or(int id, int n, bool v) {
    uint32_t r;
    asm volatile("{\n.reg .pred p, q;\nsetp.ne.u32 q, %3, 0;\nbarrier.cta.red.or.pred p, %1, %2, q;\nselp.u32 %0, 1, 0, p;\n}"
                 : "=r"(r) : "r"(id), "r"(n), "r"((uint32_t)v) : "memory");
    return r;
}

__device__ __forceinline__ int layout_list(uint32_t sb, int t, int last) {
    int tot[10];
    {
        const uint4 a = lds128(sb + GCNT), b = lds128(sb + GCNT + 16);
        const uint2 c = lds64(sb + GCNT + 32);
        tot[0] = a.x; tot[1] = a.y; tot[2] = a.z; tot[3] = a.w; tot[4] = b.x; tot[5] = b.y; tot[6] = b.z; tot[7] = b.w;
        tot[8] = c.x; tot[9] = c.y;
    }
    int run = 0, myend = 0, gap = 0, tab = 0, mx = 0;
#pragma unroll
    for (int g = 0; g < 10; g++) {
        const int ge = run + ((tot[g] + 15) & ~15);
        const int off = t * 16 - run;
        if (off >= 0 && t * 16 < ge) tab = ((g * CAPG + off) << 16) | (tot[g] - off);
        if (g == t) myend = ge;
        if (g == 4) gap = ge;
        mx = max(mx, tot[g]);
        run = ge + (g == 4 ? 48 : 0);
    }
    if (mx > CAPG || run > CAP_STEPS * 16) return -1;
    if (t < CAP_STEPS) sts32(sb + CNT_OFF + t * 4, tab);
    if (t < 48) sts32(sb + MR_OFF + ((run >> 4) + (t >> 4)) * 128 + ((t & 15) >> 1) * 16 + (t & 1) * 4, 0xFFFFFFFFu);
    if (t < 10) sts32(sb + MISC_OFF + t * 4, myend >> 4);
    if (t == 10) sts32(sb + MISC_OFF + 40, (gap >> 4) + 3);
    if (t == 11) sts32(sb + MISC_OFF + 44, last);
    return run;
}

__device__ __forceinline__ void expand_meta(uint32_t sb, int t, int p_begin, int p_end) {
#pragma unroll 2
    for (int pos = p_begin + t; pos < p_end; pos += N_AUX) {
        const uint32_t tb = lds32(sb + CNT_OFF + (pos >> 4) * 4);
        const int k = pos & 15, st16 = pos & ~15;
        const bool v = k < (int)(tb & 0xFFFF);
        const uint32_t idx = v ? (tb >> 16) + k : 0;
        const uint32_t w = lds32(sb + EL_OFF + idx * 4);
        uint32_t row;
        asm volatile("ld.shared.u8 %0, [%1];" : "=r"(row) : "r"(sb + ER_OFF + idx));
        const uint32_t se = w & 0xFFFFFF, sn = se / EPC;
        const uint32_t dbf = v ? bf16_bits_of_int((w >> 24) & 7) : DBF_INV;
        const uint32_t mr = sb + MR_OFF + st16 * 8 + (k & 7) * 16 + (k >> 3) * 4;
        sts32(mr, v ? sn : 0xFFFFFFFFu);
        sts32(mr + 8, dbf * 0x10001u);
        sts16(sb + MQ_OFF + (st16 + ((k & 7) >> 1) * 4 + (k & 1) + 2 * (k >> 3)) * 2, dbf);
        sts32(sb + CAND_OFF + pos * 4, v ? ((row - sn) * EPC + se) * 32 : 0xFFFFFFFFu);
    }
}

__device__ __forceinline__ void gather_attr_range(uint32_t sb, int t, int p_begin, int p_end, const __nv_bfloat16* __restrict__ e_attr) {
    const int h = t & 1, p0 = p_begin + (t >> 1);
    const char* base = (const char*)e_attr + h * 16;
    uint32_t src = sb + CAND_OFF + p0 * 4;
    uint32_t dst = sb + EATTR_OFF + p0 * 32 + ((h ^ ((p0 >> 2) & 1)) << 4);
#pragma unroll 1
    for (int pos = p0; pos < p_end; pos += 2 * 64) {
        uint32_t off[2];
#pragma unroll
        for (int i = 0; i < 2; i++) off[i] = lds32(src + i * 256);
#pragma unroll
        for (int i = 0; i < 2; i++) {
            if (pos + i * 64 < p_end)
                asm volatile("{\n.reg .pred p;\n.reg .b32 n, o;\n.reg .b64 a;\nsetp.ne.u32 p, %1, 0xFFFFFFFF;\nselp.b32 n, 16, 0, p;\n"
                             "selp.b32 o, %1, 0, p;\ncvt.u64.u32 a, o;\nadd.u64 a, a, %2;\ncp.async.cg.shared.global [%0], [a], 16, n;\n}"
                             ::"r"(dst + i * 2048), "r"(off[i]), "l"(base) : "memory");
        }
        src += 512;
        dst += 4096;
    }
}
template <bool WAIT_XFREE>
__device__ __forceinline__ void publish_list(uint32_t sb, int t, int run, const __nv_bfloat16* __restrict__ e_attr, uint32_t bar_rest) {
    const int s5 = lds32(sb + MISC_OFF + 40) * 16;
    const int h0 = min((int)lds32(sb + MISC_OFF) * 16 + 48, s5), h5 = min((int)lds32(sb + MISC_OFF + 20) * 16 + 48, run);
    expand_meta(sb, t, 0, h0);
    expand_meta(sb, t, s5, h5);
    bar_arrive(BAR_META, N_MAIN + N_AUX);
    bar_sync(BAR_AUX, N_AUX);
    if (WAIT_XFREE) bar_sync(BAR_XFREE, N_AUX + 32);
    gather_attr_range(sb, t, 0, h0, e_attr);
    gather_attr_range(sb, t, s5, h5, e_attr);
    cp_async_wait_all();
    bar_arrive(BAR_READY, N_MAIN + N_AUX);
    expand_meta(sb, t, h0, s5);
    expand_meta(sb, t, h5, run);
    bar_sync(BAR_AUX, N_AUX);
    gather_attr_range(sb, t, h0, s5, e_attr);
    gather_attr_range(sb, t, h5, run, e_attr);
    cp_async_wait_all();
    __syncwarp();
    if ((t & 31) == 0) mbar_arrive(bar_rest);
}

struct Params {
    const __nv_bfloat16* e_attr;
    const int* src;
    const int* dst;
    const __nv_bfloat16* g_w;
    const __nv_bfloat16* v_w;
    const __nv_bfloat16* u_w;
    __nv_bfloat16* out;
    uint4* tab;
    uint4* slots;
    unsigned int* bar;
    float4* part;
};

__global__ void __launch_bounds__(NTHREADS, 1)
egc_kernel(const __grid_constant__ CUtensorMap tm_x, const __grid_constant__ CUtensorMap tm_g,
           const __grid_constant__ CUtensorMap tm_v, const __grid_constant__ CUtensorMap tm_u,
           const __grid_constant__ CUtensorMap tm_t, const __grid_constant__ CUtensorMap tm_c,
           const __grid_constant__ CUtensorMap tm_s, const __grid_constant__ CUtensorMap tm_s2,
           const __grid_constant__ Params P) {
    extern __shared__ __align__(1024) unsigned char smem_raw[];
    const uint32_t sb = (uint32_t)__cvta_generic_to_shared(smem_raw);
    if (sb & 1023u) __trap();
    const int tid = threadIdx.x, warp = tid >> 5, lane = tid & 31;
    const int tile = blockIdx.x;
    const uint32_t bar_full = sb + BAR_OFF, bar_empty = bar_full + 8 * NST, bar_x = bar_empty + 8 * NST, bar_idx = bar_x + 32, bar_c = bar_idx + 8, bar_cand = bar_c + 8, bar_rest = bar_cand + 8;
    const __nv_bfloat16* __restrict__ e_attr = P.e_attr;

    int4 dv, sv;
    if (warp < 16) {
        if (tid < EPC / 4) {
            asm volatile("ld.global.nc.v4.s32 {%0,%1,%2,%3}, [%4];" : "=r"(dv.x), "=r"(dv.y), "=r"(dv.z), "=r"(dv.w)
                         : "l"((const int4*)P.dst + tile * (EPC / 4) + tid));
            asm volatile("ld.global.nc.v4.s32 {%0,%1,%2,%3}, [%4];" : "=r"(sv.x), "=r"(sv.y), "=r"(sv.z), "=r"(sv.w)
                         : "l"((const int4*)P.src + tile * (EPC / 4) + tid));
        }
        sts128(sb + CAND_OFF + tid * 16, make_uint4(REC_INV, REC_INV, REC_INV, REC_INV));
        sts128(sb + CAND_OFF + (tid + 512) * 16, make_uint4(REC_INV, REC_INV, REC_INV, REC_INV));
        if (tid < 128) sts32(sb + CNT_OFF + tid * 4, 0);
    } else if (warp < 20) {
        if (tid < N_MAIN + 16) sts32(sb + GCNT + (tid - N_MAIN) * 4, 0);
    } else if (tid == 640) {
        asm volatile("prefetch.tensormap [%0];" ::"l"(&tm_g) : "memory");
#pragma unroll
        for (int s = 0; s < NST; s++) {
            mbar_init(bar_full + 8 * s, 1);
            mbar_init(bar_empty + 8 * s, 16);
        }
        asm volatile("fence.mbarrier_init.release.cluster;" ::: "memory");
#pragma unroll 1
        for (int it = 0; it < NST; it++) {
            mbar_expect_tx(bar_full + 8 * it, 32768);
            tma_3d(sb + RING_OFF + it * 32768, &tm_g, 0, 256 + it * 64, 0, bar_full + 8 * it);
        }
    } else if (tid == 704) {
        asm volatile("prefetch.tensormap [%0];" ::"l"(&tm_x) : "memory");
#pragma unroll
        for (int s = 0; s < 4; s++) mbar_init(bar_x + 8 * s, 1);
        mbar_init(bar_idx, EPC / 128);
        mbar_init(bar_c, 1);
        mbar_init(bar_cand, 1);
        mbar_init(bar_rest, 4);
        asm volatile("fence.mbarrier_init.release.cluster;" ::: "memory");
#pragma unroll 1
        for (int c = 0; c < X_EARLY; c++) {
            mbar_expect_tx(bar_x + 8 * c, 10240);
            tma_2d(sb + X_OFF + c * 10240, &tm_x, c * 64, tile * TILE, bar_x + 8 * c);
        }
    } else if (tid == 672) {
        asm volatile("prefetch.tensormap [%0];" ::"l"(&tm_v) : "memory");
        asm volatile("prefetch.tensormap [%0];" ::"l"(&tm_u) : "memory");
        asm volatile("prefetch.tensormap [%0];" ::"l"(&tm_t) : "memory");
        asm volatile("prefetch.tensormap [%0];" ::"l"(&tm_c) : "memory");
        asm volatile("prefetch.tensormap [%0];" ::"l"(&tm_s) : "memory");
        asm volatile("prefetch.tensormap [%0];" ::"l"(&tm_s2) : "memory");
        const int go = tile * 2176, vo = tile * 1056;
        const int gn = min(2176, 528 * 512 - go), vn = min(1056, 256 * 512 - vo);
        if (gn > 0) asm volatile("cp.async.bulk.prefetch.L2.global [%0], %1;" ::"l"((const char*)P.g_w + go), "r"(gn) : "memory");
        if (vn > 0) {
            asm volatile("cp.async.bulk.prefetch.L2.global [%0], %1;" ::"l"((const char*)P.v_w + vo), "r"(vn) : "memory");
            asm volatile("cp.async.bulk.prefetch.L2.global [%0], %1;" ::"l"((const char*)P.u_w + vo), "r"(vn) : "memory");
        }
    }
    __syncthreads();

    if (warp >= 20) {
        asm volatile("setmaxnreg.dec.sync.aligned.u32 24;");
        if (tid == 640) {
            int st = 0, par = 0;
#pragma unroll 1
            for (int it = NST; it < NIT; it++) {
                const int p = it >> 2;
                const CUtensorMap* m = (p == 1) ? &tm_v : (p == 3) ? &tm_u : &tm_g;
                const int row = ((p == 0) ? 256 : 0) + (it & 3) * 64;
                mbar_wait(bar_empty + 8 * st, par);
                mbar_expect_tx(bar_full + 8 * st, 32768);
                tma_3d(sb + RING_OFF + st * 32768, m, 0, row, 0, bar_full + 8 * st);
                if (++st == NST) { st = 0; par ^= 1; }
            }
        } else if (tid == 704) {
            if (X_EARLY < 4) mbar_wait(bar_idx, 0);
#pragma unroll 1
            for (int c = X_EARLY; c < 4; c++) {
                mbar_expect_tx(bar_x + 8 * c, 10240);
                tma_2d(sb + X_OFF + c * 10240, &tm_x, c * 64, tile * TILE, bar_x + 8 * c);
            }
            mbar_expect_tx(bar_c, 8192);
            tma_3d(sb + CT_OFF, &tm_c, 0, 512, 0, bar_c);
        } else if (warp == 21) {
            mbar_wait(bar_full + 8 * 1, 0);
            mbar_wait(bar_full + 8 * 1, 1);
#pragma unroll 1
            for (int i = lane; i < EPC * 32 / 128; i += 32)
                asm volatile("prefetch.global.L2 [%0];" ::"l"((const char*)e_attr + (size_t)tile * EPC * 32 + i * 128) : "memory");
        } else if (warp == 23) {
            unsigned int target = 0;
            if (lane == 0) target = grid_target(P.bar);
#pragma unroll 1
            for (int wave = 0; wave < 2; wave++) {
                bar_sync(BAR_TABLE, N_MAIN + 32);
                if (lane == 0) {
#pragma unroll 1
                    for (int ds = 0; ds < 8; ds++) {
                        asm volatile("cp.async.bulk.tensor.4d.global.shared::cta.bulk_group [%0, {%2, %3, %4, %5}], [%1];"
                                     ::"l"(&tm_t), "r"(sb + EATTR_OFF + ds * 5120), "r"(0), "r"(tile * TILE), "r"(ds), "r"(wave) : "memory");
                        asm volatile("cp.async.bulk.commit_group;" ::: "memory");
                        asm volatile("cp.async.bulk.wait_group.read %0;" ::"n"(STORE_QUEUE) : "memory");
                    }
                    asm volatile("cp.async.bulk.wait_group.read 0;" ::: "memory");
                }
                __syncwarp();
                if (wave == 0) bar_arrive(BAR_STG, N_MAIN + 32);
                else bar_arrive(BAR_XFREE, N_AUX + 32);
            }
            if (lane == 0) {
                asm volatile("cp.async.bulk.wait_group 0;" ::: "memory");
                grid_arrive_relaxed(P.bar);
                grid_wait(P.bar, target);
            }
            __syncwarp();
            bar_arrive(BAR_GO, N_MAIN + 32);
        }
    } else if (warp >= 16) {
        asm volatile("setmaxnreg.dec.sync.aligned.u32 40;");
        const int t = tid - N_MAIN;
        unsigned int target = 0;
        if (t == 0) target = grid_target(P.bar + 32);
        bar_sync(BAR_S1, N_MAIN + N_AUX);
        if (t == 0) {
            asm volatile("cp.async.bulk.tensor.3d.global.shared::cta.bulk_group [%0, {%2, %3, %2}], [%1];"
                         ::"l"(&tm_s), "r"(sb + CAND_OFF), "r"(0), "r"(tile) : "memory");
            asm volatile("cp.async.bulk.commit_group;" ::: "memory");
            asm volatile("cp.async.bulk.wait_group 0;" ::: "memory");
            grid_arrive_relaxed(P.bar + 32);
            grid_wait(P.bar + 32, target);
            asm volatile("fence.proxy.async.global;" ::: "memory");
            mbar_expect_tx(bar_cand, NT * 128);
            asm volatile("cp.async.bulk.tensor.4d.shared::cluster.global.mbarrier::complete_tx::bytes [%0], [%1, {%3, %3, %3, %4}], [%2];"
                         ::"r"(sb + CAND_OFF), "l"(&tm_s2), "r"(bar_cand), "r"(0), "r"(tile) : "memory");
        }
        const uint32_t row = sb + CAND_OFF + t * 32;
        mbar_wait(bar_cand, 0);
        bool ovf = false;
#pragma unroll 1
        for (int j = 0; j < 4; j++) {
            uint4 a = make_uint4(REC_INV, REC_INV, REC_INV, REC_INV), b = a;
            if (t < NT) { a = lds128(row + j * (NT * 32)); b = lds128(row + j * (NT * 32) + 16); }
            if (j >= 2 && !__any_sync(0xffffffffu, rec_dl(a.x) != 127)) break;
            const uint32_t rec[8] = {a.x, a.y, a.z, a.w, b.x, b.y, b.z, b.w};
            uint32_t rank[8];
#pragma unroll
            for (int i = 0; i < 8; i++) rank[i] = bin_rank(sb, rec[i]);
#pragma unroll
            for (int i = 0; i < 8; i++) bin_store(sb, rec[i], rank[i], t);
            ovf |= rec_dl(b.w) == 126;
        }
        ovf = bar_or(BAR_AUX, N_AUX, ovf);
        int run = ovf ? -1 : layout_list(sb, t, 1);
        if (run >= 0) {
            bar_sync(BAR_AUX, N_AUX);
            publish_list<true>(sb, t, run, e_attr, bar_rest);
        } else {
            bar_sync(BAR_AUX, N_AUX);
            if (t < 16) sts32(sb + GCNT + t * 4, 0);
            bar_sync(BAR_AUX, N_AUX);
            bool first = true;
#pragma unroll 1
            for (int w0 = 0; w0 < NT * EPC; w0 += 128) {
                const int e = w0 + t, d = __ldg(P.dst + e), b = (unsigned)d / TILE;
                uint32_t w = REC_INV;
                const int c = (unsigned)e / EPC;
                if (b == tile) w = ((uint32_t)(d - b * TILE) << 24) | (__ldg(P.src + e) * EPC + (e - c * EPC));
                bin_store(sb, w, bin_rank(sb, w), c);
                bar_sync(BAR_AUX, N_AUX);
                int mx = 0, sum = 0;
#pragma unroll 1
                for (int g = 0; g < 10; g++) { const int v = lds32(sb + GCNT + g * 4); mx = max(mx, v); sum += v; }
                const bool fin = w0 + 128 >= NT * EPC;
                const bool flush = fin || mx > CAPG - 128 || sum > CAP_STEPS * 16 - 48 - 150 - 128;
                bar_sync(BAR_AUX, N_AUX);
                if (flush) {
                    if (first) bar_sync(BAR_XFREE, N_AUX + 32);
                    first = false;
                    run = layout_list(sb, t, fin);
                    bar_sync(BAR_AUX, N_AUX);
                    publish_list<false>(sb, t, run, e_attr, bar_rest);
                    if (!fin) bar_sync(BAR_CONSUMED, N_MAIN + N_AUX);
                    bar_sync(BAR_AUX, N_AUX);
                    if (t < 16) sts32(sb + GCNT + t * 4, 0);
                    bar_sync(BAR_AUX, N_AUX);
                }
            }
        }
    } else {
        asm volatile("setmaxnreg.inc.sync.aligned.u32 104;");
        const int wg = warp >> 2;
        const int r = lane >> 2, q = lane & 3;
        if (tid < EPC / 4) {
            const int dd[4] = {dv.x, dv.y, dv.z, dv.w};
            const int ss[4] = {sv.x, sv.y, sv.z, sv.w};
            uint32_t rank[4];
            int bb[4];
#pragma unroll
            for (int i = 0; i < 4; i++) {
                bb[i] = (unsigned)dd[i] / TILE;
                asm volatile("atom.shared.add.u32 %0, [%1], 1;" : "=r"(rank[i]) : "r"(sb + CNT_OFF + bb[i] * 4) : "memory");
            }
#pragma unroll
            for (int i = 0; i < 4; i++) {
                const uint32_t rec = ((uint32_t)(dd[i] - bb[i] * TILE) << 24) | (ss[i] * EPC + tid * 4 + i);
                sts32(sb + CAND_OFF + bb[i] * 128 + (min(rank[i], 31u) << 2), rank[i] < 31 ? rec : REC_OVF);
            }
            __syncwarp();
            if (lane == 0) mbar_arrive(bar_idx);
        }
        asm volatile("fence.proxy.async.shared::cta;" ::: "memory");
        bar_arrive(BAR_S1, N_MAIN + N_AUX);

        float d[40];
        uint32_t pB[20], pV[20], xa[20];
        const uint64_t da0 = smem_desc(sb + RING_OFF + wg * 8192), db0 = smem_desc(sb + X_OFF);

        auto stage = [&](const int it) {
            const int c = it & 3, st = it % NST;
            if (it < 4) mbar_wait(bar_x + 8 * c, 0);
            mbar_wait(bar_full + 8 * st, (it / NST) & 1);
            wgmma_fence();
            const uint64_t da = da0 + st * 2048, db = db0 + c * 640;
            wgmma_n80(d, da, db, c != 0);
            wgmma_n80(d, da + 128, db + 2, 1);
            wgmma_n80(d, da + 256, db + 4, 1);
            wgmma_n80(d, da + 384, db + 6, 1);
            wgmma_commit();
        };
        auto release = [&](const int it) {
            if (it + NST < NIT && lane == 0) mbar_arrive(bar_empty + 8 * (it % NST));
        };

        auto stage_table = [&](const uint32_t (&pk)[20]) {
            const int nd = lane & 7, m = lane >> 3;
            const uint32_t base = sb + EATTR_OFF + (warp >> 1) * 5120 + ((m >> 1) * 8 + nd) * 64 +
                                  ((((warp & 1) * 2 + (m & 1)) ^ ((nd >> 1) & 3)) << 4);
#pragma unroll
            for (int jj = 0; jj < 5; jj++)
                asm volatile("stmatrix.sync.aligned.m8n8.x4.trans.shared.b16 [%0], {%1,%2,%3,%4};"
                             ::"r"(base + jj * 1024), "r"(pk[4 * jj]), "r"(pk[4 * jj + 1]), "r"(pk[4 * jj + 2]), "r"(pk[4 * jj + 3]) : "memory");
            asm volatile("fence.proxy.async.shared::cta;" ::: "memory");
            bar_arrive(BAR_TABLE, N_MAIN + 32);
        };
        uint32_t cf[2][4];
        auto load_cf = [&]() {
            mbar_wait(bar_c, 0);
#pragma unroll
        for (int c = 0; c < 2; c++) {
            const int k = (lane >> 4) * 8 + (lane & 7), col = (warp & 7) * 32 + c * 16 + ((lane >> 3) & 1) * 8;
            asm volatile("ldmatrix.sync.aligned.m8n8.x4.trans.shared.b16 {%0,%1,%2,%3}, [%4];"
                         : "=r"(cf[c][0]), "=r"(cf[c][1]), "=r"(cf[c][2]), "=r"(cf[c][3])
                         : "r"(sb + CT_OFF + (col >> 6) * 2048 + k * 128 + ((((col & 63) >> 3) ^ (k & 7)) << 4)));
#pragma unroll
            for (int i = 0; i < 4; i++) asm("mul.rn.bf16x2 %0, %0, %1;" : "+r"(cf[c][i]) : "r"(0x3F003F00u));
        }
        };
#pragma unroll
        for (int p = 0; p < 4; p++) {
#pragma unroll
            for (int c = 0; c < 4; c++) {
                stage(p * 4 + c);
                if (p == 1 && c == 0) stage_table(pB);
                if (p == 2 && c == 0) { load_cf(); bar_sync(BAR_STG, N_MAIN + 32); stage_table(pV); }
                if (c > 0) { wgmma_wait<1>(); release(p * 4 + c - 1); }
            }
            wgmma_wait<0>();
            release(p * 4 + 3);
            if (p == 0) {
#pragma unroll
                for (int j = 0; j < 20; j++) pB[j] = pack_bf16(0.5f * d[2 * j], 0.5f * d[2 * j + 1]);
            } else if (p == 1) {
#pragma unroll
                for (int j = 0; j < 20; j++) pV[j] = pack_bf16(0.5f * d[2 * j], 0.5f * d[2 * j + 1]);
            } else if (p == 2) {
#pragma unroll
                for (int j = 0; j < 20; j++) xa[j] = pack_bf16(0.5f * d[2 * j], 0.5f * d[2 * j + 1]);
            }
        }

        bar_sync(BAR_MAIN, N_MAIN);
#pragma unroll
        for (int j = 0; j < 10; j++) {
            asm volatile("st.shared.v2.u32 [%0], {%1, %2};" ::"r"(sb + PARK_U + (warp * 10 + j) * 256 + lane * 8),
                         "r"(pack_bf16(d[4 * j], d[4 * j + 1])), "r"(pack_bf16(d[4 * j + 2], d[4 * j + 3])) : "memory");
            asm volatile("st.shared.v2.u32 [%0], {%1, %2};" ::"r"(sb + PARK_XA + (warp * 10 + j) * 256 + lane * 8), "r"(xa[2 * j]), "r"(xa[2 * j + 1]) : "memory");
        }
        bar_sync(BAR_MAIN, N_MAIN);

        {
            const int ds = warp & 7, set = warp >> 3;
            const uint32_t cA = bf16_bits_of_int(2 * q) | (bf16_bits_of_int(2 * q + 1) << 16);
            const uint32_t cB = bf16_bits_of_int(r) * 0x10001u;
            uint32_t id0, id1, id2, id3;
            {
                const uint32_t v = (r == 2 * q ? 0x00003F80u : 0u) | (r == 2 * q + 1 ? 0x3F800000u : 0u);
                asm volatile("mov.u32 %0, %4;\nmov.u32 %1, 0;\nmov.u32 %2, 0;\nmov.u32 %3, %4;" : "=r"(id0), "=r"(id1), "=r"(id2), "=r"(id3) : "r"(v));
            }
            const char* tabl = (const char*)P.tab + ds * 128 + (lane & 7) * 16;
            const int ek = (lane >> 4) * 8 + (lane & 7);
            const uint32_t ea_l = sb + EATTR_OFF + ek * 32 + ((((lane >> 3) & 1) ^ ((ek >> 2) & 1)) << 4);
            const uint32_t mr_l = sb + MR_OFF + r * 16;
            const uint32_t mq_l = sb + MQ_OFF + q * 8;
            const uint32_t bounce = sb + CAND_OFF + warp * 512;
            const uint32_t pk = sb + (ds * 20 + set * 5) * 256 + lane * 8;
            float4* const part = P.part + ((size_t)tile * 160 + ds * 20 + set * 5) * 32 + lane;

            const uint32_t yb = warp < 14 ? sb + YB_OFF + warp * 4096 : sb + CAND_OFF + 8192 + (warp - 14) * 4096;
            const int g8 = lane >> 3;
            const uint32_t y_dst = yb + g8 * 128 + (((lane & 7) ^ g8) << 4);
            const uint32_t y_dst2 = yb + (g8 + 4) * 128 + (((lane & 7) ^ (g8 + 4)) << 4);
            const uint32_t mw_l = sb + MR_OFF + g8 * 16;
            const uint32_t y_ldb = yb + (lane & 7) * 128 + (((lane >> 3) ^ (lane & 7)) << 4);
            const uint32_t y_ldv = y_ldb ^ 64;

            auto gather1 = [&](uint32_t dst, uint32_t w) {
                asm volatile("{\n.reg .pred p;\n.reg .b64 a;\nsetp.ge.s32 p, %1, 0;\nmad.wide.u32 a, %1, 1024, %2;\n"
                             "@p cp.async.cg.shared.global [%0], [a], 16;\n}" ::"r"(dst), "r"(w), "l"(tabl) : "memory");
            };

            bar_sync(BAR_GO, N_MAIN + 32);
            for (int pass = 0;; pass++) {
                bar_sync(BAR_META, N_MAIN + N_AUX);
                const int last = lds32(sb + MISC_OFF + 44);
                int i = set ? (int)lds32(sb + MISC_OFF + 40) : 0;
                uint32_t pe = ea_l + i * 512, pr = mr_l + i * 128, pq = mq_l + i * 32;
                auto gather_step = [&](const int k, const int off) {
                    const uint32_t pw = pr - mr_l + mw_l + off;
                    const uint2 wa = lds64(pw), wb = lds64(pw + 64);
                    gather1(y_dst + k * 2048, wa.x);
                    gather1(y_dst2 + k * 2048, wb.x);
                    gather1(y_dst + k * 2048 + 1024, wa.y);
                    gather1(y_dst2 + k * 2048 + 1024, wb.y);
                    asm volatile("cp.async.commit_group;" ::: "memory");
                };
                {
#pragma unroll
                    for (int k = 0; k < 8; k++) sts128(yb + lane * 16 + k * 512, make_uint4(0, 0, 0, 0));
                    __syncwarp();
                    gather_step(0, 0);
                    gather_step(1, 128);
                }
                uint32_t xb[2][4], hv[2][4];
                auto fetch = [&](const int k, const int off) {
                    asm volatile("cp.async.wait_group 1;" ::: "memory");
                    __syncwarp();
#pragma unroll
                    for (int t = 0; t < 2; t++) {
                        asm volatile("ldmatrix.sync.aligned.m8n8.x4.shared.b16 {%0,%1,%2,%3}, [%4];"
                                     : "=r"(xb[t][0]), "=r"(xb[t][1]), "=r"(xb[t][2]), "=r"(xb[t][3]) : "r"(y_ldb + k * 2048 + t * 1024) : "memory");
                        asm volatile("ldmatrix.sync.aligned.m8n8.x4.trans.shared.b16 {%0,%1,%2,%3}, [%4];"
                                     : "=r"(hv[t][0]), "=r"(hv[t][1]), "=r"(hv[t][2]), "=r"(hv[t][3]) : "r"(y_ldv + k * 2048 + t * 1024) : "memory");
                    }
                    gather_step(k, off);
                };
                fetch(0, 2 * 128);
                bar_sync(BAR_READY, N_MAIN + N_AUX);
                int ph = 0;
                for (int g = 0; g < 5; g++) {
                    const int gend = lds32(sb + MISC_OFF + (set * 5 + g) * 4);
                    float acc[2][4];
                    uint2 xf[2];
#pragma unroll
                    for (int c = 0; c < 2; c++) {
                        if (pass == 0) {
                            const uint2 u = lds64(pk + PARK_U + (c * 10 + g) * 256);
                            acc[c][0] = __uint_as_float(u.x << 16); acc[c][1] = __uint_as_float(u.x & 0xFFFF0000u);
                            acc[c][2] = __uint_as_float(u.y << 16); acc[c][3] = __uint_as_float(u.y & 0xFFFF0000u);
                        } else {
                            const float4 a = part[(c * 10 + g) * 32];
                            acc[c][0] = a.x; acc[c][1] = a.y; acc[c][2] = a.z; acc[c][3] = a.w;
                        }
                        xf[c] = lds64(pk + PARK_XA + (c * 10 + g) * 256);
                    }

                    auto step = [&](const int k) {
                        const uint2 dd = lds64(pr + k * 128 + 8);
                        const uint2 db = lds64(pq + k * 32);
                        uint32_t e[4];
                        asm volatile("ldmatrix.sync.aligned.m8n8.x4.shared.b16 {%0,%1,%2,%3}, [%4];"
                                     : "=r"(e[0]), "=r"(e[1]), "=r"(e[2]), "=r"(e[3]) : "r"(pe + k * 512));
                        const uint32_t sa0 = seteq_bf16x2(dd.x, cA), sa1 = seteq_bf16x2(dd.y, cA);
                        const uint32_t sb0 = seteq_bf16x2(db.x, cB), sb1 = seteq_bf16x2(db.y, cB);
#pragma unroll
                        for (int c = 0; c < 2; c++) {
                            float p0[4], p1[4];
                            mma_bf16(p0, cf[c][0], cf[c][1], cf[c][2], cf[c][3], e[0], e[1], 0.f, 0.f, 0.f, 0.f);
                            mma_bf16(p1, cf[c][0], cf[c][1], cf[c][2], cf[c][3], e[2], e[3], 0.f, 0.f, 0.f, 0.f);
                            mma_bf16_k8(p0, xf[c].x, xf[c].y, sa0);
                            mma_bf16_k8(p1, xf[c].x, xf[c].y, sa1);
                            mma_bf16(p0, id0, id1, id2, id3, xb[0][2 * c], xb[0][2 * c + 1], p0[0], p0[1], p0[2], p0[3]);
                            mma_bf16(p1, id0, id1, id2, id3, xb[1][2 * c], xb[1][2 * c + 1], p1[0], p1[1], p1[2], p1[3]);
                            const uint32_t m0 = fma_bf16x2(hv[0][2 * c], pack_bf16(tanh_approx(p0[0]), tanh_approx(p0[1])), hv[0][2 * c]);
                            const uint32_t m1 = fma_bf16x2(hv[0][2 * c + 1], pack_bf16(tanh_approx(p0[2]), tanh_approx(p0[3])), hv[0][2 * c + 1]);
                            const uint32_t m2 = fma_bf16x2(hv[1][2 * c], pack_bf16(tanh_approx(p1[0]), tanh_approx(p1[1])), hv[1][2 * c]);
                            const uint32_t m3 = fma_bf16x2(hv[1][2 * c + 1], pack_bf16(tanh_approx(p1[2]), tanh_approx(p1[3])), hv[1][2 * c + 1]);
                            mma_bf16(acc[c], m0, m1, m2, m3, sb0, sb1, acc[c][0], acc[c][1], acc[c][2], acc[c][3]);
                        }
                        fetch(k ^ 1, (k + 3) * 128);
                    };

                    int rem = gend - i;
                    i = gend;
                    while (rem > 0) {
                        if (ph == 0) {
                            step(0);
                            ph = 1;
                            if (--rem == 0) break;
                        }
                        step(1);
                        ph = 0; pe += 2 * 512; pr += 2 * 128; pq += 2 * 32; --rem;
                    }

                    if (g == 0) mbar_wait(bar_rest, pass & 1);

                    if (last) {
                        uint32_t o[4];
#pragma unroll
                        for (int c = 0; c < 2; c++) {
                            float z[4];
#pragma unroll
                            for (int j = 0; j < 4; j++) z[j] = __fdividef(acc[c][j], 1.f + __expf(-acc[c][j]));
                            o[2 * c] = pack_bf16(z[0], z[1]);
                            o[2 * c + 1] = pack_bf16(z[2], z[3]);
                        }
                        asm volatile("stmatrix.sync.aligned.m8n8.x4.trans.shared.b16 [%0], {%1,%2,%3,%4};"
                                     ::"r"(bounce + (lane & 7) * 64 + (((lane >> 3) ^ ((lane >> 1) & 3)) << 4)),
                                       "r"(o[0]), "r"(o[1]), "r"(o[2]), "r"(o[3]) : "memory");
                        __syncwarp();
                        const int node = lane >> 2;
                        const uint4 v = lds128(bounce + node * 64 + ((q ^ ((node >> 1) & 3)) << 4));
                        *(uint4*)(P.out + (size_t)(tile * TILE + (set * 5 + g) * 8 + node) * DD + ds * 32 + q * 8) = v;
                        __syncwarp();
                    } else {
#pragma unroll
                        for (int c = 0; c < 2; c++) part[(c * 10 + g) * 32] = make_float4(acc[c][0], acc[c][1], acc[c][2], acc[c][3]);
                    }
                }
                if (last) break;
                cp_async_wait_all();
                bar_arrive(BAR_CONSUMED, N_MAIN + N_AUX);
            }
        }
    }
}

typedef CUresult (*EncodeFn)(CUtensorMap*, CUtensorMapDataType, cuuint32_t, void*, const cuuint64_t*, const cuuint64_t*,
                             const cuuint32_t*, const cuuint32_t*, CUtensorMapInterleave, CUtensorMapSwizzle,
                             CUtensorMapL2promotion, CUtensorMapFloatOOBfill);

static void make_map(EncodeFn fn, CUtensorMap* m, const void* ptr, int rows, int box_rows) {
    cuuint64_t dims[2] = {(cuuint64_t)DD, (cuuint64_t)rows};
    cuuint64_t strides[1] = {(cuuint64_t)DD * 2};
    cuuint32_t box[2] = {64, (cuuint32_t)box_rows};
    cuuint32_t es[2] = {1, 1};
    fn(m, CU_TENSOR_MAP_DATA_TYPE_BFLOAT16, 2, const_cast<void*>(ptr), dims, strides, box, es, CU_TENSOR_MAP_INTERLEAVE_NONE,
       CU_TENSOR_MAP_SWIZZLE_128B, CU_TENSOR_MAP_L2_PROMOTION_L2_256B, CU_TENSOR_MAP_FLOAT_OOB_FILL_NONE);
}

static void make_tmap(EncodeFn fn, CUtensorMap* m, void* ptr) {
    cuuint64_t dims[4] = {32, (cuuint64_t)NN, 8, 2};
    cuuint64_t strides[3] = {1024, 128, 64};
    cuuint32_t box[4] = {32, (cuuint32_t)TILE, 1, 1};
    cuuint32_t es[4] = {1, 1, 1, 1};
    fn(m, CU_TENSOR_MAP_DATA_TYPE_BFLOAT16, 4, ptr, dims, strides, box, es, CU_TENSOR_MAP_INTERLEAVE_NONE,
       CU_TENSOR_MAP_SWIZZLE_64B, CU_TENSOR_MAP_L2_PROMOTION_NONE, CU_TENSOR_MAP_FLOAT_OOB_FILL_NONE);
}

static void make_smap(EncodeFn fn, CUtensorMap* m, void* ptr) {
    cuuint64_t dims[3] = {32, (cuuint64_t)NT, (cuuint64_t)NT};
    cuuint64_t strides[2] = {128, (cuuint64_t)NT * 128};
    cuuint32_t box[3] = {32, 1, (cuuint32_t)NT};
    cuuint32_t es[3] = {1, 1, 1};
    fn(m, CU_TENSOR_MAP_DATA_TYPE_UINT32, 3, ptr, dims, strides, box, es, CU_TENSOR_MAP_INTERLEAVE_NONE,
       CU_TENSOR_MAP_SWIZZLE_NONE, CU_TENSOR_MAP_L2_PROMOTION_NONE, CU_TENSOR_MAP_FLOAT_OOB_FILL_NONE);
}

static void make_smap2(EncodeFn fn, CUtensorMap* m, void* ptr) {
    cuuint64_t dims[4] = {8, (cuuint64_t)NT, 4, (cuuint64_t)NT};
    cuuint64_t strides[3] = {128, 32, (cuuint64_t)NT * 128};
    cuuint32_t box[4] = {8, (cuuint32_t)NT, 4, 1};
    cuuint32_t es[4] = {1, 1, 1, 1};
    fn(m, CU_TENSOR_MAP_DATA_TYPE_UINT32, 4, ptr, dims, strides, box, es, CU_TENSOR_MAP_INTERLEAVE_NONE,
       CU_TENSOR_MAP_SWIZZLE_NONE, CU_TENSOR_MAP_L2_PROMOTION_NONE, CU_TENSOR_MAP_FLOAT_OOB_FILL_NONE);
}

static void make_wmap(EncodeFn fn, CUtensorMap* m, const void* ptr, int rows, int box_rows) {
    cuuint64_t dims[3] = {64, (cuuint64_t)rows, 4};
    cuuint64_t strides[2] = {(cuuint64_t)DD * 2, 128};
    cuuint32_t box[3] = {64, (cuuint32_t)box_rows, 4};
    cuuint32_t es[3] = {1, 1, 1};
    fn(m, CU_TENSOR_MAP_DATA_TYPE_BFLOAT16, 3, const_cast<void*>(ptr), dims, strides, box, es, CU_TENSOR_MAP_INTERLEAVE_NONE,
       CU_TENSOR_MAP_SWIZZLE_128B, CU_TENSOR_MAP_L2_PROMOTION_L2_256B, CU_TENSOR_MAP_FLOAT_OOB_FILL_NONE);
}

}

extern "C" void kernel_launch(void* const* d_in, const int* in_sizes, int n_in, void* d_out, int out_size) {
    using namespace egc;
    (void)in_sizes; (void)n_in; (void)out_size;
    static EncodeFn encode = nullptr;
    static void *p_tab = nullptr, *p_slots = nullptr, *p_bar = nullptr, *p_part = nullptr;
    if (!encode) {
        void* fn = nullptr;
        cudaDriverEntryPointQueryResult qr;
        cudaGetDriverEntryPoint("cuTensorMapEncodeTiled", &fn, cudaEnableDefault, &qr);
        encode = (EncodeFn)fn;
        cudaFuncSetAttribute(egc_kernel, cudaFuncAttributeMaxDynamicSharedMemorySize, SMEM_BYTES);
        cudaGetSymbolAddress(&p_tab, g_tab);
        cudaGetSymbolAddress(&p_slots, g_slots);
        cudaGetSymbolAddress(&p_bar, g_bar);
        cudaGetSymbolAddress(&p_part, g_part);
    }
    const __nv_bfloat16* x = (const __nv_bfloat16*)d_in[0];
    Params P;
    P.e_attr = (const __nv_bfloat16*)d_in[1];
    P.src = (const int*)d_in[2];
    P.dst = (const int*)d_in[3];
    P.u_w = (const __nv_bfloat16*)d_in[4];
    P.v_w = (const __nv_bfloat16*)d_in[5];
    P.g_w = (const __nv_bfloat16*)d_in[6];
    P.out = (__nv_bfloat16*)d_out;
    P.tab = (uint4*)p_tab;
    P.slots = (uint4*)p_slots;
    P.bar = (unsigned int*)p_bar;
    P.part = (float4*)p_part;
    CUtensorMap tx, tg, tv, tu, tt, tc, ts, ts2;
    make_smap(encode, &ts, p_slots);
    make_smap2(encode, &ts2, p_slots);
    make_tmap(encode, &tt, p_tab);
    make_map(encode, &tx, x, NN, TILE);
    make_wmap(encode, &tg, P.g_w, 2 * DD + 16, 64);
    make_wmap(encode, &tc, P.g_w, 2 * DD + 16, 16);
    make_wmap(encode, &tv, P.v_w, DD, 64);
    make_wmap(encode, &tu, P.u_w, DD, 64);
    egc_kernel<<<NT, NTHREADS, SMEM_BYTES, cudaStreamPerThread>>>(tx, tg, tv, tu, tt, tc, ts, ts2, P);
}
```
